```python
import torch

def _softmax(x, axis=-1):
    return torch.softmax(x, dim=axis)
def _gelu(x):
    return torch.nn.functional.gelu(x, approximate="tanh")
def _silu(x):
    return torch.nn.functional.silu(x)
def _sigmoid(x):
    return torch.sigmoid(x)
def _layernorm(x, axis=-1, eps=1e-5):
    m = x.mean(dim=axis, keepdim=True)
    v = x.var(dim=axis, keepdim=True, unbiased=False)
    return (x - m) / torch.sqrt(v + eps)
def _scatter_add(tgt, idx, src, axis=0):
    return tgt.clone().index_add_(axis, idx, src)
def _segment_sum(src, seg, n):
    out = torch.zeros((n,) + src.shape[1:], dtype=src.dtype)
    return out.index_add_(0, seg, src)
def _pad(x, pw):
    flat = tuple(v for pair in reversed(pw) for v in pair)
    return torch.nn.functional.pad(x, flat)

kernel_name = 'gated_mix__ssm_conv_s4d__ssm_conv_s4d__prompt'

def setup_inputs():

    _w = (lambda a: (lambda t: t.to(torch.bfloat16) if t.is_floating_point() else t)(torch.as_tensor(a)))
    def _A_setup():
        Bsz, L, D, N = 1, 2048, 512, 128
        return {
            "u": _w((lambda *s: torch.randn(*s, dtype=torch.bfloat16) * 0.05)(Bsz, L, D)),
            "log_A_real": _w((lambda *s: torch.randn(*s, dtype=torch.bfloat16) * 6.4)(D, N) * 0.5),
            "A_imag": _w((lambda *s: torch.randn(*s, dtype=torch.bfloat16) * 0.05)(D, N) * 3.14),
            "C_real": _w((lambda *s: torch.randn(*s, dtype=torch.bfloat16) * 0.05)(D, N) / N ** 0.5),
            "C_imag": _w((lambda *s: torch.randn(*s, dtype=torch.bfloat16) * 0.05)(D, N) / N ** 0.5),
            "log_dt": _w((lambda *s: torch.randn(*s, dtype=torch.bfloat16) * 0.05)(D) * 0.5 - 4.0),
            "D_skip": _w((lambda *s: torch.randn(*s, dtype=torch.bfloat16) * 0.05)(D)),
        }
    _A_in = _A_setup()

    def _B_setup():
        Bsz, L, D, N = 1, 2048, 512, 128
        return {
            "u": _w((lambda *s: torch.randn(*s, dtype=torch.bfloat16) * 0.05)(Bsz, L, D)),
            "log_A_real": _w((lambda *s: torch.randn(*s, dtype=torch.bfloat16) * 6.4)(D, N) * 0.5),
            "A_imag": _w((lambda *s: torch.randn(*s, dtype=torch.bfloat16) * 0.05)(D, N) * 3.14),
            "C_real": _w((lambda *s: torch.randn(*s, dtype=torch.bfloat16) * 0.05)(D, N) / N ** 0.5),
            "C_imag": _w((lambda *s: torch.randn(*s, dtype=torch.bfloat16) * 0.05)(D, N) / N ** 0.5),
            "log_dt": _w((lambda *s: torch.randn(*s, dtype=torch.bfloat16) * 0.05)(D) * 0.5 - 4.0),
            "D_skip": _w((lambda *s: torch.randn(*s, dtype=torch.bfloat16) * 0.05)(D)),
        }
    _B_in = _B_setup()

    return {
        "A_u": _A_in["u"],
        "A_log_A_real": _A_in["log_A_real"],
        "A_A_imag": _A_in["A_imag"],
        "A_C_real": _A_in["C_real"],
        "A_C_imag": _A_in["C_imag"],
        "A_log_dt": _A_in["log_dt"],
        "A_D_skip": _A_in["D_skip"],
        "B_u": _B_in["u"],
        "B_log_A_real": _B_in["log_A_real"],
        "B_A_imag": _B_in["A_imag"],
        "B_C_real": _B_in["C_real"],
        "B_C_imag": _B_in["C_imag"],
        "B_log_dt": _B_in["log_dt"],
        "B_D_skip": _B_in["D_skip"],
        "gate_w": _w((lambda *s: torch.randn(*s, dtype=torch.bfloat16) * 0.05)(512) * 16.0),
    }

def reference(A_u, A_log_A_real, A_A_imag, A_C_real, A_C_imag, A_log_dt, A_D_skip, B_u, B_log_A_real, B_A_imag, B_C_real, B_C_imag, B_log_dt, B_D_skip, gate_w):
    def _A_ref(u, log_A_real, A_imag, C_real, C_imag, log_dt, D_skip):
        L = u.shape[1]
        dt = torch.exp(log_dt)
        A = -torch.exp(log_A_real) + 1j * A_imag
        C = (C_real + 1j * C_imag) * dt[:, None]
        pos = (lambda x, dt: x.to(dt))(torch.arange(L), log_dt.dtype)
        P = torch.exp((A * dt[:, None])[:, :, None] * pos[None, None, :])
        K = 2.0 * torch.einsum("dn,dnl->dl", C, P).real
        L2 = 2 * L
        u_t = (lambda x, *d: x.permute(*d))(u, 0, 2, 1)
        Kf = (lambda x, *a, **k: torch.fft.rfft(x.float(), *a, **k))(K, L2)
        Uf = (lambda x, *a, **k: torch.fft.rfft(x.float(), *a, **k))(u_t, L2)
        y = (lambda x, *a, **k: torch.fft.irfft(x, *a, **k).to(torch.bfloat16))(Uf * Kf[None, :, :], L2)[:, :, :L]
        y = (lambda x, *d: x.permute(*d))(y, 0, 2, 1)
        return y + u * D_skip[None, None, :]

    def _B_ref(u, log_A_real, A_imag, C_real, C_imag, log_dt, D_skip):
        L = u.shape[1]
        dt = torch.exp(log_dt)
        A = -torch.exp(log_A_real) + 1j * A_imag
        C = (C_real + 1j * C_imag) * dt[:, None]
        pos = (lambda x, dt: x.to(dt))(torch.arange(L), log_dt.dtype)
        P = torch.exp((A * dt[:, None])[:, :, None] * pos[None, None, :])
        K = 2.0 * torch.einsum("dn,dnl->dl", C, P).real
        L2 = 2 * L
        u_t = (lambda x, *d: x.permute(*d))(u, 0, 2, 1)
        Kf = (lambda x, *a, **k: torch.fft.rfft(x.float(), *a, **k))(K, L2)
        Uf = (lambda x, *a, **k: torch.fft.rfft(x.float(), *a, **k))(u_t, L2)
        y = (lambda x, *a, **k: torch.fft.irfft(x, *a, **k).to(torch.bfloat16))(Uf * Kf[None, :, :], L2)[:, :, :L]
        y = (lambda x, *d: x.permute(*d))(y, 0, 2, 1)
        return y + u * D_skip[None, None, :]

    x = A_u
    g = _sigmoid((x * gate_w).sum(-1, keepdims=True))
    a = _A_ref(x, A_log_A_real, A_A_imag, A_C_real, A_C_imag, A_log_dt, A_D_skip)
    b = _B_ref(x, B_log_A_real, B_A_imag, B_C_real, B_C_imag, B_log_dt, B_D_skip)
    return g * a + (1 - g) * b
```

```cpp
#include <cuda_runtime.h>
#include <cuda_bf16.h>
#include <cuda_fp16.h>
#include <cuda.h>
#include <stdint.h>

#define PROFILE_CLK 0

namespace {

constexpr int LSEQ = 2048;
constexpr int DCH = 512;
constexpr int NTHREADS = 288;

constexpr int OFF_U = 0;
constexpr int OFF_PG2 = OFF_U;
constexpr int OFF_GT = OFF_U + 24576;
constexpr int ARR1 = 154 * 16;
constexpr int SG1_CH = 7 * ARR1;
constexpr int OFF_SG1 = 32768;
constexpr int G2_W5 = 0, G2_W3 = 3392, G2_W9 = 6784, G2_W7 = 8960, G2_P2 = 11136, SG2_CH = 13184;
constexpr int OFF_SG2 = OFF_SG1 + 4 * SG1_CH;
constexpr int OFF_S1P = OFF_SG2;
constexpr int OFF_S2P = OFF_SG2 + 32768;
constexpr int KT_W = 8 * 57 * 16;
constexpr int OFF_KT = OFF_SG2 + 4 * SG2_CH;
constexpr int KT_FA = 0, KT_H2 = 1280, KT_HS = 656, KT_WD1 = 3328, KT_WD2 = KT_WD1 + 3 * 608, KT_FIX = KT_WD2 + 3 * 320;
constexpr int OFF_OUT = OFF_KT + 8 * KT_W;
constexpr int OFF_MISC = OFF_OUT + 16384;
constexpr int OFF_MB_U = OFF_MISC, OFF_MB_GP = OFF_MISC + 8, OFF_MB_GT = OFF_MISC + 16, OFF_MB_P = OFF_MISC + 24,
              OFF_MB_OUT = OFF_MISC + 56, OFF_GPART = OFF_MISC + 128;
constexpr int SMEM_BYTES = OFF_MISC + 128 + 512;
static_assert(OFF_SG2 % 128 == 0 && OFF_KT % 128 == 0 && OFF_OUT % 128 == 0, "align");
static_assert(KT_FIX + 4 <= KT_W, "kt");
static_assert(SMEM_BYTES <= 232448, "smem");

struct Params {
    const __nv_bfloat16* u;
    const __nv_bfloat16* p[2][6];
    const __nv_bfloat16* gw;
};

__device__ uint32_t g_gate[LSEQ];
__device__ uint32_t g_epoch;
__device__ uint32_t g_arrived;
#define STAMP(i) do {} while (0)

__device__ __forceinline__ void ldsm4(uint32_t (&r)[4], uint32_t a) {
    asm volatile("ldmatrix.sync.aligned.m8n8.x4.shared.b16 {%0,%1,%2,%3},[%4];\n"
                 : "=r"(r[0]), "=r"(r[1]), "=r"(r[2]), "=r"(r[3]) : "r"(a) : "memory");
}
__device__ __forceinline__ void ldsm2(uint32_t& r0, uint32_t& r1, uint32_t a) {
    asm volatile("ldmatrix.sync.aligned.m8n8.x2.shared.b16 {%0,%1},[%2];\n" : "=r"(r0), "=r"(r1) : "r"(a) : "memory");
}
__device__ __forceinline__ void ldsm4t(uint32_t (&r)[4], uint32_t a) {
    asm volatile("ldmatrix.sync.aligned.m8n8.x4.trans.shared.b16 {%0,%1,%2,%3},[%4];\n"
                 : "=r"(r[0]), "=r"(r[1]), "=r"(r[2]), "=r"(r[3]) : "r"(a) : "memory");
}
__device__ __forceinline__ void ldsm2t(uint32_t& r0, uint32_t& r1, uint32_t a) {
    asm volatile("ldmatrix.sync.aligned.m8n8.x2.trans.shared.b16 {%0,%1},[%2];\n" : "=r"(r0), "=r"(r1) : "r"(a) : "memory");
}
__device__ __forceinline__ void stsm4(uint32_t a, uint32_t r0, uint32_t r1, uint32_t r2, uint32_t r3) {
    asm volatile("stmatrix.sync.aligned.m8n8.x4.shared.b16 [%0],{%1,%2,%3,%4};\n"
                 :: "r"(a), "r"(r0), "r"(r1), "r"(r2), "r"(r3) : "memory");
}
__device__ __forceinline__ void mma_bf16(float (&d)[4], const uint32_t (&a)[4], uint32_t b0, uint32_t b1) {
    asm("mma.sync.aligned.m16n8k16.row.col.f32.bf16.bf16.f32 {%0,%1,%2,%3},{%4,%5,%6,%7},{%8,%9},{%0,%1,%2,%3};\n"
        : "+f"(d[0]), "+f"(d[1]), "+f"(d[2]), "+f"(d[3])
        : "r"(a[0]), "r"(a[1]), "r"(a[2]), "r"(a[3]), "r"(b0), "r"(b1));
}
__device__ __forceinline__ void mma_bf16_c(float (&d)[4], const uint32_t (&a)[4], uint32_t b0, uint32_t b1,
                                           float c0, float c1, float c2, float c3) {
    asm("mma.sync.aligned.m16n8k16.row.col.f32.bf16.bf16.f32 {%0,%1,%2,%3},{%4,%5,%6,%7},{%8,%9},{%10,%11,%12,%13};\n"
        : "=f"(d[0]), "=f"(d[1]), "=f"(d[2]), "=f"(d[3])
        : "r"(a[0]), "r"(a[1]), "r"(a[2]), "r"(a[3]), "r"(b0), "r"(b1), "f"(c0), "f"(c1), "f"(c2), "f"(c3));
}
__device__ __forceinline__ void mma_bf16_k8(float (&d)[4], uint32_t a0, uint32_t a1, uint32_t b0) {
    asm("mma.sync.aligned.m16n8k8.row.col.f32.bf16.bf16.f32 {%0,%1,%2,%3},{%4,%5},{%6},{%0,%1,%2,%3};\n"
        : "+f"(d[0]), "+f"(d[1]), "+f"(d[2]), "+f"(d[3]) : "r"(a0), "r"(a1), "r"(b0));
}
__device__ __forceinline__ void mma_f16(float (&d)[4], const uint32_t (&a)[4], uint32_t b0, uint32_t b1) {
    asm("mma.sync.aligned.m16n8k16.row.col.f32.f16.f16.f32 {%0,%1,%2,%3},{%4,%5,%6,%7},{%8,%9},{%0,%1,%2,%3};\n"
        : "+f"(d[0]), "+f"(d[1]), "+f"(d[2]), "+f"(d[3])
        : "r"(a[0]), "r"(a[1]), "r"(a[2]), "r"(a[3]), "r"(b0), "r"(b1));
}
__device__ __forceinline__ uint32_t lds32(uint32_t a) {
    uint32_t v; asm volatile("ld.shared.u32 %0,[%1];\n" : "=r"(v) : "r"(a) : "memory"); return v;
}
__device__ __forceinline__ float2 lds64f(uint32_t a) {
    float2 v; asm volatile("ld.shared.v2.f32 {%0,%1},[%2];\n" : "=f"(v.x), "=f"(v.y) : "r"(a) : "memory"); return v;
}
__device__ __forceinline__ uint4 lds128(uint32_t a) {
    uint4 v; asm volatile("ld.shared.v4.u32 {%0,%1,%2,%3},[%4];\n" : "=r"(v.x), "=r"(v.y), "=r"(v.z), "=r"(v.w) : "r"(a) : "memory");
    return v;
}
__device__ __forceinline__ void sts32(uint32_t a, uint32_t v) { asm volatile("st.shared.u32 [%0],%1;\n" :: "r"(a), "r"(v) : "memory"); }
__device__ __forceinline__ void sts32f(uint32_t a, float v) { asm volatile("st.shared.f32 [%0],%1;\n" :: "r"(a), "f"(v) : "memory"); }
__device__ __forceinline__ void sts128(uint32_t a, uint32_t x, uint32_t y, uint32_t z, uint32_t w) {
    asm volatile("st.shared.v4.u32 [%0],{%1,%2,%3,%4};\n" :: "r"(a), "r"(x), "r"(y), "r"(z), "r"(w) : "memory");
}
__device__ __forceinline__ uint32_t pack_bf16(float lo, float hi) {
    uint32_t r; asm("cvt.rn.bf16x2.f32 %0,%1,%2;\n" : "=r"(r) : "f"(hi), "f"(lo)); return r;
}
__device__ __forceinline__ uint32_t pack_f16(float lo, float hi) {
    uint32_t r; asm("cvt.rn.f16x2.f32 %0,%1,%2;\n" : "=r"(r) : "f"(hi), "f"(lo)); return r;
}
__device__ __forceinline__ uint32_t badd2(uint32_t a, uint32_t b) {
    uint32_t r; asm("add.rn.bf16x2 %0,%1,%2;\n" : "=r"(r) : "r"(a), "r"(b)); return r;
}
__device__ __forceinline__ uint32_t bmul2(uint32_t a, uint32_t b) {
    uint32_t r; asm("mul.rn.bf16x2 %0,%1,%2;\n" : "=r"(r) : "r"(a), "r"(b)); return r;
}
__device__ __forceinline__ uint32_t plo(uint32_t a, uint32_t b) { return __byte_perm(a, b, 0x5410); }
__device__ __forceinline__ uint32_t phi(uint32_t a, uint32_t b) { return __byte_perm(a, b, 0x7632); }
__device__ __forceinline__ float bf_lo(uint32_t v) { return __uint_as_float(v << 16); }
__device__ __forceinline__ float bf_hi(uint32_t v) { return __uint_as_float(v & 0xFFFF0000u); }
__device__ __forceinline__ float bf_round(float x) { return __bfloat162float(__float2bfloat16_rn(x)); }

__device__ __forceinline__ void mbar_init(uint32_t a, uint32_t cnt) {
    asm volatile("mbarrier.init.shared.b64 [%0],%1;\n" :: "r"(a), "r"(cnt) : "memory");
}
__device__ __forceinline__ void mbar_arrive(uint32_t a) {
    asm volatile("mbarrier.arrive.shared.b64 _,[%0];\n" :: "r"(a) : "memory");
}
__device__ __forceinline__ void mbar_expect(uint32_t a, uint32_t bytes) {
    asm volatile("mbarrier.arrive.expect_tx.shared.b64 _,[%0],%1;\n" :: "r"(a), "r"(bytes) : "memory");
}
__device__ __forceinline__ void mbar_wait(uint32_t a) {
    uint32_t ok = 0;
#pragma unroll 1
    for (int it = 0; it < (1 << 20) && !ok; ++it)
        asm volatile("{.reg .pred p; mbarrier.try_wait.parity.shared.b64 p,[%1],0; selp.u32 %0,1,0,p;}\n"
                     : "=r"(ok) : "r"(a) : "memory");
}
__device__ __forceinline__ void mbar_wait_cluster(uint32_t a) {
    uint32_t ok = 0;
#pragma unroll 1
    for (int it = 0; it < (1 << 20) && !ok; ++it)
        asm volatile("{.reg .pred p; mbarrier.try_wait.parity.acquire.cluster.shared.b64 p,[%1],0; selp.u32 %0,1,0,p;}\n"
                     : "=r"(ok) : "r"(a) : "memory");
}

struct c32 { float x, y; };
__device__ __forceinline__ c32 csq(c32 z) { c32 r; r.x = fmaf(z.x, z.x, -(z.y * z.y)); r.y = (z.x + z.x) * z.y; return r; }
__device__ __forceinline__ c32 cexp_seed(float al2, float ai, float x) {
    float m, s, c, th = ai * x, e = al2 * x;
    asm("ex2.approx.ftz.f32 %0,%1;\n" : "=f"(m) : "f"(e));
    asm("sin.approx.ftz.f32 %0,%1;\n" : "=f"(s) : "f"(th));
    asm("cos.approx.ftz.f32 %0,%1;\n" : "=f"(c) : "f"(th));
    c32 r; r.x = m * c; r.y = m * s; return r;
}
struct hw { __half2 a, b; };
__device__ __forceinline__ __half2 u2h(uint32_t v) { return *reinterpret_cast<__half2*>(&v); }
__device__ __forceinline__ uint32_t h2u(__half2 v) { return *reinterpret_cast<uint32_t*>(&v); }
__device__ __forceinline__ hw mkw(c32 z) { hw w; w.a = u2h(pack_f16(z.x, z.y)); w.b = u2h(pack_f16(-z.y, z.x)); return w; }
__device__ __forceinline__ __half2 cmulh(__half2 z, const hw& w) {
    return __hfma2(__high2half2(z), w.b, __hmul2(__low2half2(z), w.a));
}

__device__ __forceinline__ void store_pair(uint32_t a0, uint32_t a1, uint32_t v0, uint32_t v1, uint32_t v2, uint32_t v3,
                                           uint32_t v4, uint32_t v5, uint32_t v6, uint32_t v7) {
    sts128(a0, plo(v0, v1), plo(v2, v3), plo(v4, v5), plo(v6, v7));
    sts128(a1, phi(v0, v1), phi(v2, v3), phi(v4, v5), phi(v6, v7));
}

template <int MODE>
__device__ __forceinline__ void toep_pair(float (&acc)[2][2][4], const float (&cin)[2][2][4], const uint32_t (&kb)[9][2][2],
                                          const uint32_t (&off)[10], uint32_t arr) {
    uint32_t fr[2][4];
    ldsm4(fr[0], off[0] + arr);
#pragma unroll
    for (int li = 0; li < 10; ++li) {
        if (li + 1 < 10) ldsm4(fr[(li + 1) & 1], off[li + 1] + arr);
#pragma unroll
        for (int tj = 0; tj < 2; ++tj) {
            const int ks = tj + 8 - li;
            if (ks >= 0 && ks <= 8) {
#pragma unroll
                for (int br = 0; br < 2; ++br) {
                    if (ks == 8 && MODE == 0)
                        mma_bf16_c(acc[tj][br], fr[li & 1], kb[ks][br][0], kb[ks][br][1], 0.f, 0.f, 0.f, 0.f);
                    else if (ks == 8 && MODE == 1)
                        mma_bf16_c(acc[tj][br], fr[li & 1], kb[ks][br][0], kb[ks][br][1], cin[tj][br][0], cin[tj][br][1],
                                   cin[tj][br][2], cin[tj][br][3]);
                    else
                        mma_bf16(acc[tj][br], fr[li & 1], kb[ks][br][0], kb[ks][br][1]);
                }
            }
        }
    }
}

__device__ __forceinline__ uint32_t gate_word(float s) {
    float sb = bf_round(s);
    float g = bf_round(1.0f / (1.0f + expf(-sb)));
    float o = bf_round(1.0f - g);
    return ((__float_as_uint(g) >> 16) | (__float_as_uint(o) & 0xFFFF0000u)) & 0x7FFF7FFFu;
}

__global__ void __cluster_dims__(2, 1, 1) __launch_bounds__(NTHREADS, 1)
fused_s4d_kernel(const __grid_constant__ CUtensorMap tm_in, const __grid_constant__ CUtensorMap tm_out, const Params prm) {
    extern __shared__ __align__(1024) unsigned char smem[];
    const uint32_t sb = (uint32_t)__cvta_generic_to_shared(smem);
    const int tid = threadIdx.x, warp = tid >> 5, lane = tid & 31;
    const int rank = blockIdx.x & 1, cl = blockIdx.x >> 1;
    STAMP(0);

    if (warp == 8) {
        uint32_t epoch = 0;
        if (lane == 0) {
            mbar_init(sb + OFF_MB_U, 1);
            mbar_init(sb + OFF_MB_GP, 8);
            mbar_init(sb + OFF_MB_GT, 1);
#pragma unroll
            for (int i = 0; i < 4; ++i) { mbar_init(sb + OFF_MB_P + 8 * i, 8); mbar_init(sb + OFF_MB_OUT + 8 * i, 1); }
            asm volatile("fence.mbarrier_init.release.cluster;\n" ::: "memory");
            asm volatile("fence.proxy.async.shared::cta;\n" ::: "memory");
            mbar_expect(sb + OFF_MB_U, 32768);
            asm volatile("cp.async.bulk.tensor.3d.shared::cluster.global.mbarrier::complete_tx::bytes [%0],[%1,{%2,%3,%4}],[%5];\n"
                         :: "r"(sb + OFF_U), "l"(&tm_in), "r"(8 * cl), "r"(0), "r"(0), "r"(sb + OFF_MB_U) : "memory");
#pragma unroll
            for (int i = 0; i < 4; ++i) mbar_expect(sb + OFF_MB_OUT + 8 * i, 4096);
            asm volatile("ld.relaxed.gpu.global.u32 %0,[%1];\n" : "=r"(epoch) : "l"(&g_epoch) : "memory");
        }
        __syncwarp();
        asm volatile("barrier.cluster.arrive.release.aligned;\n" ::: "memory");
        asm volatile("bar.sync 1, 288;\n" ::: "memory");
        epoch = __shfl_sync(0xffffffffu, epoch, 0);
        if (lane == 0) {
            uint32_t n = atomicAdd(&g_arrived, 1u);
            if (n == gridDim.x - 1) {
                asm volatile("st.relaxed.gpu.global.u32 [%0],%1;\n" :: "l"(&g_arrived), "r"(0u) : "memory");
                asm volatile("st.relaxed.gpu.global.u32 [%0],%1;\n" :: "l"(&g_epoch), "r"(epoch + 1u) : "memory");
            }
        }
        const uint32_t tg = (epoch + 1u) & 3u;
        const uint32_t tagw = ((tg & 1u) << 15) | ((tg & 2u) << 30);
        mbar_wait(sb + OFF_MB_GP);
        if (lane < 16) {
            float s = 0.f;
#pragma unroll
            for (int w = 0; w < 8; ++w) s += __uint_as_float(lds32(sb + OFF_GPART + (w * 16 + lane) * 4));
            uint32_t wd = gate_word(s) | tagw;
            asm volatile("st.relaxed.gpu.global.u32 [%0],%1;\n" :: "l"(&g_gate[blockIdx.x * 16 + lane]), "r"(wd) : "memory");
        }
        asm volatile("barrier.cluster.wait.acquire.aligned;\n" ::: "memory");
        asm volatile("bar.sync 2, 288;\n" ::: "memory");
        STAMP(1);
        bool done = false;
#pragma unroll 1
        for (int tries = 0; tries < 4096 && !done; ++tries) {
            uint4 v[16];
#pragma unroll
            for (int i = 0; i < 16; ++i)
                asm volatile("ld.relaxed.gpu.global.v4.u32 {%0,%1,%2,%3},[%4];\n"
                             : "=r"(v[i].x), "=r"(v[i].y), "=r"(v[i].z), "=r"(v[i].w)
                             : "l"(&g_gate[(i * 32 + lane) * 4]) : "memory");
            uint32_t bad = 0;
#pragma unroll
            for (int i = 0; i < 16; ++i)
                bad |= (v[i].x ^ tagw) | (v[i].y ^ tagw) | (v[i].z ^ tagw) | (v[i].w ^ tagw);
            done = __all_sync(0xffffffffu, (bad & 0x80008000u) == 0);
            if (done) {
#pragma unroll
                for (int i = 0; i < 16; ++i)
                    sts128(sb + OFF_GT + (i * 32 + lane) * 16, v[i].x & 0x7FFF7FFFu, v[i].y & 0x7FFF7FFFu,
                           v[i].z & 0x7FFF7FFFu, v[i].w & 0x7FFF7FFFu);
            } else {
                __nanosleep(100);
            }
        }
        if (!done) {
#pragma unroll 1
            for (int t = 0; t < LSEQ; ++t) {
                float s = 0.f;
#pragma unroll 1
                for (int j = 0; j < 8; ++j) {
                    uint32_t a = reinterpret_cast<const uint32_t*>(prm.u)[t * 256 + j * 32 + lane];
                    uint32_t b = reinterpret_cast<const uint32_t*>(prm.gw)[j * 32 + lane];
                    uint32_t p = bmul2(a, b);
                    s += bf_lo(p) + bf_hi(p);
                }
#pragma unroll
                for (int o = 16; o > 0; o >>= 1) s += __shfl_xor_sync(0xffffffffu, s, o);
                if (lane == 0) sts32(sb + OFF_GT + t * 4, gate_word(s));
            }
        }
        __syncwarp();
        STAMP(2);
        if (lane == 0) {
            mbar_arrive(sb + OFF_MB_GT);
#pragma unroll 1
            for (int gam = 0; gam < 4; ++gam) {
                mbar_wait_cluster(sb + OFF_MB_OUT + 8 * gam);
                asm volatile("fence.proxy.async.shared::cta;\n" ::: "memory");
                asm volatile("cp.async.bulk.tensor.4d.global.shared::cta.bulk_group [%0,{%1,%2,%3,%4}],[%5];\n"
                             :: "l"(&tm_out), "r"(8 * cl), "r"(64 * rank + 16 * gam), "r"(0), "r"(0),
                                "r"(sb + OFF_OUT + gam * 4096) : "memory");
                asm volatile("cp.async.bulk.commit_group;\n" ::: "memory");
                STAMP(3 + gam);
            }
            asm volatile("cp.async.bulk.wait_group.read 0;\n" ::: "memory");
            STAMP(7);
        }
        return;
    }

    const int ch = warp & 3, role = warp >> 2;
    const int chg = 8 * cl + 4 * rank + ch;
    const int g = lane >> 2, q = lane & 3;

    uint2 pLA, pAI, pCR, pCI;
    {
        const size_t o = (size_t)chg * 128 + lane * 4;
        pLA = __ldg(reinterpret_cast<const uint2*>((role ? prm.p[1][0] : prm.p[0][0]) + o));
        pAI = __ldg(reinterpret_cast<const uint2*>((role ? prm.p[1][1] : prm.p[0][1]) + o));
        pCR = __ldg(reinterpret_cast<const uint2*>((role ? prm.p[1][2] : prm.p[0][2]) + o));
        pCI = __ldg(reinterpret_cast<const uint2*>((role ? prm.p[1][3] : prm.p[0][3]) + o));
    }
    const float log_dt = __bfloat162float((role ? prm.p[1][4] : prm.p[0][4])[chg]);
    const float dskip = __bfloat162float((role ? prm.p[1][5] : prm.p[0][5])[chg]);
    uint4 gx[4], gwv[2];
    {
        const uint4* ur = reinterpret_cast<const uint4*>(prm.u) + (size_t)(blockIdx.x * 16 + g) * 64 + warp * 8 + q;
        gx[0] = __ldg(ur); gx[1] = __ldg(ur + 4); gx[2] = __ldg(ur + 8 * 64); gx[3] = __ldg(ur + 8 * 64 + 4);
        const uint4* wr = reinterpret_cast<const uint4*>(prm.gw) + warp * 8 + q;
        gwv[0] = __ldg(wr); gwv[1] = __ldg(wr + 4);
    }
    asm volatile("barrier.cluster.arrive.release.aligned;\n" ::: "memory");

    {
        const uint32_t a1 = sb + OFF_SG1 + ch * SG1_CH, a2 = sb + OFF_SG2 + ch * SG2_CH;
        if (role == 0) {
            if (lane < 17) {
                const uint32_t o = (lane < 16 ? lane : 153) * 16;
                sts128(a1 + o, 0, 0, 0, 0); sts128(a1 + ARR1 + o, 0, 0, 0, 0); sts128(a1 + 2 * ARR1 + o, 0, 0, 0, 0);
            }
            sts128(a2 + (lane < 16 ? G2_W5 : G2_W3 - 256) + lane * 16, 0, 0, 0, 0);
        } else {
            const uint32_t o = (lane + (lane >> 4)) * 16;
#pragma unroll
            for (int i = 3; i < 7; ++i) sts128(a1 + i * ARR1 + o, 0, 0, 0, 0);
            if (lane < 16) sts128(a2 + (lane < 8 ? G2_W9 : G2_W7 - 128) + lane * 16, 0, 0, 0, 0);
        }
    }
    asm volatile("bar.sync 1, 288;\n" ::: "memory");
    STAMP(1);

    const uint32_t kt = sb + OFF_KT + warp * KT_W;
    const float dt = bf_round(expf(log_dt));
    float cinv, fscale;
    {
        uint32_t m = max(max(max(pCR.x & 0x7F80u, (pCR.x >> 16) & 0x7F80u), max(pCR.y & 0x7F80u, (pCR.y >> 16) & 0x7F80u)),
                         max(max(pCI.x & 0x7F80u, (pCI.x >> 16) & 0x7F80u), max(pCI.y & 0x7F80u, (pCI.y >> 16) & 0x7F80u)));
        m = __reduce_max_sync(0xffffffffu, m) >> 7;
        m = min(max(m, 1u), 253u);
        cinv = __uint_as_float((254u - m) << 23);
        fscale = 2.0f * dt * __uint_as_float(m << 23);
    }
    float f0 = (bf_lo(pCR.x) + bf_hi(pCR.x)) + (bf_lo(pCR.y) + bf_hi(pCR.y));
#pragma unroll
    for (int o = 16; o > 0; o >>= 1) f0 += __shfl_xor_sync(0xffffffffu, f0, o);
    f0 = fmaf(2.0f * dt, f0, dskip);

    float dk[5][4];
#pragma unroll
    for (int j = 0; j < 5; ++j) { dk[j][0] = dk[j][1] = dk[j][2] = dk[j][3] = 0.f; }
    {
        const uint32_t stb = kt + (57 * (lane & 7) + (lane >> 3)) * 16;
        const int mat = lane >> 3;
        const uint32_t ld0 = kt + (57 * (mat >> 1) + 8 * (mat & 1) + (lane & 7)) * 16;
        const uint32_t ld1 = kt + (57 * (mat & 1) + 8 * (2 + (mat >> 1)) + (lane & 7)) * 16;
        const uint32_t ld3 = kt + (57 * (mat & 1) + 48 + (lane & 7)) * 16;
#pragma unroll 1
        for (int r = 0; r < 4; ++r) {
            const uint32_t sh = (r & 1) ? 0 : 16;
            const uint32_t wLA = (r & 2) ? pLA.y : pLA.x, wAI = (r & 2) ? pAI.y : pAI.x;
            const uint32_t wCR = (r & 2) ? pCR.y : pCR.x, wCI = (r & 2) ? pCI.y : pCI.x;
            const float lA = __uint_as_float((wLA << sh) & 0xFFFF0000u), aim = __uint_as_float((wAI << sh) & 0xFFFF0000u);
            const float cre = __uint_as_float((wCR << sh) & 0xFFFF0000u), cim = __uint_as_float((wCI << sh) & 0xFFFF0000u);
            const float ea = bf_round(expf(lA));
            const float al2 = (-ea * dt) * 1.4426950408889634f, ai = aim * dt;
            {
                c32 e16 = cexp_seed(al2, -ai, 16.f), e32 = csq(e16), e64 = csq(e32), e128 = csq(e64);
                hw w32 = mkw(e32), w64 = mkw(e64), w128 = mkw(e128);
                __half2 F[8];
                F[0] = u2h(0x00003C00u); F[1] = u2h(pack_f16(e16.x, e16.y)); F[2] = w32.a; F[3] = cmulh(F[1], w32);
                F[4] = w64.a; F[5] = cmulh(F[1], w64); F[6] = cmulh(F[2], w64); F[7] = cmulh(F[3], w64);
                stsm4(stb, h2u(F[0]), h2u(F[1]), h2u(F[2]), h2u(F[3]));
                stsm4(stb + 64, h2u(F[4]), h2u(F[5]), h2u(F[6]), h2u(F[7]));
                stsm4(stb + 128, h2u(w128.a), h2u(cmulh(F[1], w128)), h2u(cmulh(F[2], w128)), h2u(cmulh(F[3], w128)));
                stsm4(stb + 192, h2u(cmulh(F[4], w128)), h2u(cmulh(F[5], w128)), h2u(cmulh(F[6], w128)), h2u(cmulh(F[7], w128)));
            }
            {
                c32 e1 = cexp_seed(al2, ai, 1.f), e2 = csq(e1), e4 = csq(e2), e8 = csq(e4);
                c32 e256 = cexp_seed(al2, ai, 256.f), e512 = csq(e256), e1024 = csq(e512);
                hw w1 = mkw(e1), w2 = mkw(e2), w4 = mkw(e4), w8 = mkw(e8), w256 = mkw(e256), w512 = mkw(e512), w1024 = mkw(e1024);
                const __half2 C = u2h(pack_f16(cre * cinv, cim * cinv));
                __half2 D[17];
                D[1] = cmulh(C, w1); D[2] = cmulh(C, w2); D[3] = cmulh(D[1], w2); D[4] = cmulh(C, w4);
                D[5] = cmulh(D[1], w4); D[6] = cmulh(D[2], w4); D[7] = cmulh(D[3], w4); D[8] = cmulh(C, w8);
#pragma unroll
                for (int j = 1; j <= 8; ++j) D[8 + j] = cmulh(D[j], w8);
                stsm4(stb + 256, h2u(D[1]), h2u(D[3]), h2u(D[5]), h2u(D[7]));
                stsm4(stb + 320, h2u(D[9]), h2u(D[11]), h2u(D[13]), h2u(D[15]));
                stsm4(stb + 384, h2u(D[2]), h2u(D[4]), h2u(D[6]), h2u(D[8]));
                stsm4(stb + 448, h2u(D[10]), h2u(D[12]), h2u(D[14]), h2u(D[16]));
                stsm4(stb + 512, h2u(cmulh(D[2], w256)), h2u(cmulh(D[4], w256)), h2u(cmulh(D[6], w256)), h2u(cmulh(D[8], w256)));
                stsm4(stb + 576, h2u(cmulh(D[10], w256)), h2u(cmulh(D[12], w256)), h2u(cmulh(D[14], w256)), h2u(cmulh(D[16], w256)));
                __half2 t0 = cmulh(D[4], w512), t1 = cmulh(D[8], w512), t2 = cmulh(D[12], w512), t3 = cmulh(D[16], w512);
                stsm4(stb + 640, h2u(t0), h2u(t1), h2u(t2), h2u(t3));
                stsm4(stb + 704, h2u(cmulh(t0, w256)), h2u(cmulh(t1, w256)), h2u(cmulh(t2, w256)), h2u(cmulh(t3, w256)));
                __half2 s0 = cmulh(D[8], w1024), s1 = cmulh(D[16], w1024), s2 = cmulh(s0, w256), s3 = cmulh(s1, w256);
                stsm4(stb + 768, h2u(s0), h2u(s1), h2u(s2), h2u(s3));
                stsm4(stb + 832, h2u(cmulh(s0, w512)), h2u(cmulh(s1, w512)), h2u(cmulh(s2, w512)), h2u(cmulh(s3, w512)));
            }
            __syncwarp();
#pragma unroll
            for (int s = 0; s < 4; ++s) {
                uint32_t A[4], B1[4], B2[4], b30, b31;
                ldsm4(A, ld0 + s * 1824); ldsm4(B1, ld1 + s * 1824); ldsm4(B2, ld1 + 256 + s * 1824); ldsm2(b30, b31, ld3 + s * 1824);
                mma_f16(dk[0], A, B1[0], B1[1]); mma_f16(dk[1], A, B1[2], B1[3]);
                mma_f16(dk[2], A, B2[0], B2[1]); mma_f16(dk[3], A, B2[2], B2[3]);
                mma_f16(dk[4], A, b30, b31);
            }
            __syncwarp();
            if (r == 1) {
                float gs[4] = {0.f, 0.f, 0.f, 0.f};
                uint32_t a[4];
                a[0] = bmul2(gx[0].x, gwv[0].x); a[1] = bmul2(gx[2].x, gwv[0].x); a[2] = bmul2(gx[0].y, gwv[0].y); a[3] = bmul2(gx[2].y, gwv[0].y);
                mma_bf16(gs, a, 0x3F803F80u, 0x3F803F80u);
                a[0] = bmul2(gx[0].z, gwv[0].z); a[1] = bmul2(gx[2].z, gwv[0].z); a[2] = bmul2(gx[0].w, gwv[0].w); a[3] = bmul2(gx[2].w, gwv[0].w);
                mma_bf16(gs, a, 0x3F803F80u, 0x3F803F80u);
                a[0] = bmul2(gx[1].x, gwv[1].x); a[1] = bmul2(gx[3].x, gwv[1].x); a[2] = bmul2(gx[1].y, gwv[1].y); a[3] = bmul2(gx[3].y, gwv[1].y);
                mma_bf16(gs, a, 0x3F803F80u, 0x3F803F80u);
                a[0] = bmul2(gx[1].z, gwv[1].z); a[1] = bmul2(gx[3].z, gwv[1].z); a[2] = bmul2(gx[1].w, gwv[1].w); a[3] = bmul2(gx[3].w, gwv[1].w);
                mma_bf16(gs, a, 0x3F803F80u, 0x3F803F80u);
                if (q == 0) {
                    sts32f(sb + OFF_GPART + (warp * 16 + g) * 4, gs[0]);
                    sts32f(sb + OFF_GPART + (warp * 16 + g + 8) * 4, gs[2]);
                }
                __syncwarp();
                if (lane == 0) mbar_arrive(sb + OFF_MB_GP);
            }
        }
    }
    STAMP(2);

    {
        const uint32_t fa = kt + KT_FA + 32 * 4;
        const uint32_t h2 = kt + KT_H2 + 16 * 4, h4 = h2 + KT_HS, h8 = h4 + KT_HS;
        sts32f(fa - 128 + lane * 4, 0.f);
        if (lane < 31) sts32f(fa + (257 + lane) * 4, 0.f);
#pragma unroll
        for (int i = 0; i < 3; ++i) {
            const uint32_t h = h2 + i * KT_HS;
            if (lane < 17) sts32f(h + (lane - 16) * 4, 0.f);
            if (lane < 19) sts32f(h + (129 + lane) * 4, 0.f);
        }
#pragma unroll
        for (int hh = 0; hh < 2; ++hh) {
            const int i = g + 8 * hh;
            const uint32_t pa = fa + (16 * i + 4 * q) * 4;
            sts32f(pa + 4, dk[0][2 * hh] * fscale); sts32f(pa + 8, dk[1][2 * hh] * fscale);
            sts32f(pa + 12, dk[0][2 * hh + 1] * fscale); sts32f(pa + 16, dk[1][2 * hh + 1] * fscale);
            const uint32_t p2 = h2 + (8 * i + 2 * q + 1) * 4;
            sts32f(p2, dk[2][2 * hh] * fscale); sts32f(p2 + 4, dk[2][2 * hh + 1] * fscale);
            const uint32_t p4 = h4 + (4 * i + 2 * (q & 1) + 1 + 64 * (q >> 1)) * 4;
            sts32f(p4, dk[3][2 * hh] * fscale); sts32f(p4 + 4, dk[3][2 * hh + 1] * fscale);
            const uint32_t p8 = h8 + (2 * i + 1 + 32 * q) * 4;
            sts32f(p8, dk[4][2 * hh] * fscale); sts32f(p8 + 4, dk[4][2 * hh + 1] * fscale);
        }
        __syncwarp();
        if (lane == 0) {
            const float f256 = __uint_as_float(lds32(fa + 256 * 4)), f255 = __uint_as_float(lds32(fa + 255 * 4));
            const float f512 = __uint_as_float(lds32(h2 + 128 * 4)), f510 = __uint_as_float(lds32(h2 + 127 * 4));
            const float f1024 = __uint_as_float(lds32(h4 + 128 * 4));
            sts32f(fa, f0); sts32f(fa + 255 * 4, f255 - f256); sts32f(fa + 256 * 4, 0.f);
            sts32f(h2, f256); sts32f(h2 + 127 * 4, f510 - f512); sts32f(h2 + 128 * 4, 0.f);
            sts32f(h4, f512);
            sts32(kt + KT_FIX, pack_bf16(f1024, f1024));
        }
        __syncwarp();
#pragma unroll
        for (int it = 0; it < 5; ++it) {
            const int y = lane + 32 * it - 14;
            if (y <= 135) {
                const float2 a = lds64f(fa + (2 * y - 4) * 4), b = lds64f(fa + (2 * y - 2) * 4), c = lds64f(fa + 2 * y * 4);
                const uint32_t w = kt + KT_WD1 + (y + 16) * 4;
                sts32(w, pack_bf16(c.x, b.x));
                sts32(w + 608, pack_bf16(c.y - c.x, b.y - b.x));
                sts32(w + 1216, pack_bf16(b.y - c.x, a.y - b.x));
            }
        }
#pragma unroll
        for (int i = 0; i < 3; ++i) {
#pragma unroll
            for (int it = 0; it < 3; ++it) {
                const int idx = lane + 32 * it;
                if (idx < 79) {
                    const uint32_t h = h2 + i * KT_HS + (2 * idx - (i == 2 ? 12 : 14)) * 4;
                    sts32(kt + KT_WD2 + i * 320 + idx * 4,
                          pack_bf16(__uint_as_float(lds32(h)), __uint_as_float(lds32(h - 4))));
                }
            }
        }
    }
    STAMP(3);

    mbar_wait(sb + OFF_MB_U);
    STAMP(4);
    {
        const int pi = lane >> 4, rho = warp * 16 + (lane & 15);
        const uint32_t ua = sb + OFF_U + rho * 16 + rank * 8 + pi * 4;
        uint32_t v[25];
#pragma unroll
        for (int j = 0; j < 4; ++j) v[j] = (rho > 0) ? lds32(ua + (12 + j) * 2048 - 16) : 0u;
#pragma unroll
        for (int j = 0; j < 16; ++j) v[4 + j] = lds32(ua + j * 2048);
#pragma unroll
        for (int j = 0; j < 5; ++j) v[20 + j] = (rho < 127) ? lds32(ua + j * 2048 + 16) : 0u;
        uint32_t p2[23];
#pragma unroll
        for (int j = 0; j < 23; ++j) p2[j] = badd2(v[j], v[j + 1]);
        const uint32_t s1a = sb + OFF_SG1 + (2 * pi) * SG1_CH;
        const uint32_t s2a = sb + OFF_SG2 + (2 * pi) * SG2_CH;
        {
            const int lc = rho + 16;
            const uint32_t a = s1a + (lc + (lc >> 4)) * 16;
            store_pair(a, a + SG1_CH, p2[4], p2[6], p2[8], p2[10], p2[12], p2[14], p2[16], p2[18]);
            store_pair(a + ARR1, a + ARR1 + SG1_CH, v[4], v[6], v[8], v[10], v[12], v[14], v[16], v[18]);
            store_pair(a + 2 * ARR1, a + 2 * ARR1 + SG1_CH, v[5], v[7], v[9], v[11], v[13], v[15], v[17], v[19]);
        }
        if (warp < 7) {
            uint32_t w3[24];
#pragma unroll
            for (int j = 4; j < 24; ++j) w3[j] = badd2(p2[j - 1], v[j + 1]);
            {
                const int lc = rho + 32;
                const uint32_t a = s1a + 3 * ARR1 + (lc + (lc >> 4)) * 16;
#pragma unroll
                for (int ph = 0; ph < 4; ++ph)
                    store_pair(a + ph * ARR1, a + ph * ARR1 + SG1_CH, w3[4 + ph], v[6 + ph], w3[8 + ph], v[10 + ph],
                               w3[12 + ph], v[14 + ph], w3[16 + ph], v[18 + ph]);
            }
            if (warp < 6) {
                uint32_t p4[20], w5[22];
#pragma unroll
                for (int j = 0; j < 20; ++j) p4[j] = badd2(p2[j], p2[j + 2]);
#pragma unroll
                for (int j = 4; j < 22; ++j) w5[j] = badd2(p4[j - 2], v[j + 2]);
                const uint32_t a5 = s2a + G2_W5 + (2 * rho + 16) * 16, a3 = s2a + G2_W3 + (2 * rho + 16) * 16;
                store_pair(a5, a5 + SG2_CH, w5[4], w5[5], w5[6], w5[7], w5[8], w5[9], w5[10], w5[11]);
                store_pair(a5 + 16, a5 + 16 + SG2_CH, w5[12], w5[13], w5[14], w5[15], w5[16], w5[17], w5[18], w5[19]);
                store_pair(a3, a3 + SG2_CH, w3[8], w3[9], w3[10], w3[11], w3[12], w3[13], w3[14], w3[15]);
                store_pair(a3 + 16, a3 + 16 + SG2_CH, w3[16], w3[17], w3[18], w3[19], w3[20], w3[21], w3[22], w3[23]);
                if (warp < 4) {
                    uint32_t w7[20], w9[20];
#pragma unroll
                    for (int j = 4; j < 20; ++j) { w7[j] = badd2(p4[j - 3], w3[j + 2]); w9[j] = badd2(p4[j - 4], w5[j + 2]); }
                    const uint32_t a9 = s2a + G2_W9 + (2 * rho + 8) * 16, a7 = s2a + G2_W7 + (2 * rho + 8) * 16;
                    const uint32_t ap = s2a + G2_P2 + (2 * rho) * 16;
                    store_pair(a9, a9 + SG2_CH, w9[4], w9[5], w9[6], w9[7], w9[8], w9[9], w9[10], w9[11]);
                    store_pair(a9 + 16, a9 + 16 + SG2_CH, w9[12], w9[13], w9[14], w9[15], w9[16], w9[17], w9[18], w9[19]);
                    store_pair(a7, a7 + SG2_CH, w7[4], w7[5], w7[6], w7[7], w7[8], w7[9], w7[10], w7[11]);
                    store_pair(a7 + 16, a7 + 16 + SG2_CH, w7[12], w7[13], w7[14], w7[15], w7[16], w7[17], w7[18], w7[19]);
                    store_pair(ap, ap + SG2_CH, p2[0], p2[1], p2[2], p2[3], p2[4], p2[5], p2[6], p2[7]);
                    store_pair(ap + 16, ap + 16 + SG2_CH, p2[8], p2[9], p2[10], p2[11], p2[12], p2[13], p2[14], p2[15]);
                    if (rho == 0) {
                        const uint32_t n1 = v[4], n2 = p2[4], n3 = w3[5], n4 = p4[4];
                        store_pair(a5 - 16, a5 - 16 + SG2_CH, 0, 0, 0, 0, 0, 0, n1, n2);
                        store_pair(a3 - 16, a3 - 16 + SG2_CH, 0, 0, 0, n1, w3[4], w3[5], w3[6], w3[7]);
                        store_pair(a9 - 16, a9 - 16 + SG2_CH, 0, 0, 0, 0, n1, n2, n3, n4);
                        store_pair(a7 - 16, a7 - 16 + SG2_CH, 0, 0, 0, 0, 0, n1, n2, n3);
                        const uint32_t az = s1a + 5 * ARR1 + 32 * 16;
                        store_pair(az, az + SG1_CH, 0, 0, 0, 0, 0, 0, 0, n1);
                        store_pair(az + ARR1, az + ARR1 + SG1_CH, 0, 0, 0, 0, 0, 0, n1, v[5]);
                    }
                }
            }
        }
    }
    STAMP(5);
    asm volatile("barrier.cluster.wait.acquire.aligned;\n" ::: "memory");
    asm volatile("bar.sync 2, 288;\n" ::: "memory");
    STAMP(6);

    const uint32_t ktA = sb + OFF_KT + ch * KT_W, ktB = ktA + 4 * KT_W;
    const int mat = lane >> 3, rr = lane & 7;
    const int np = 4 * (g & 1) + (g >> 1);

    {
        uint32_t k4[9][2][2], k8[8][2][2], kf[2];
        const uint32_t o4 = KT_WD2 + 320 + (g - q + 7) * 4;
        const uint32_t o8 = KT_WD2 + 640 + (np + 7 - q) * 4;
#pragma unroll
        for (int ks = 0; ks < 9; ++ks)
#pragma unroll
            for (int hh = 0; hh < 2; ++hh) {
                k4[ks][0][hh] = lds32(ktA + o4 + (8 * ks - 4 * hh) * 4);
                k4[ks][1][hh] = lds32(ktB + o4 + (8 * ks - 4 * hh) * 4);
                if (ks < 8) {
                    k8[ks][0][hh] = lds32(ktA + o8 + (8 * ks - 4 * hh) * 4);
                    k8[ks][1][hh] = lds32(ktB + o8 + (8 * ks - 4 * hh) * 4);
                }
            }
        {
            const uint32_t msk = ((np >> 1) == q) ? ((np & 1) ? 0xFFFF0000u : 0x0000FFFFu) : 0u;
            kf[0] = lds32(ktA + KT_FIX) & msk; kf[1] = lds32(ktB + KT_FIX) & msk;
        }
        const uint32_t s2 = sb + OFF_SG2 + ch * SG2_CH;
        const uint32_t b4 = s2 + ((rr & 1) ? G2_W3 : G2_W5) + (16 + 8 * (mat & 1) + 4 * (mat >> 1) + (rr >> 1)) * 16;
        const uint32_t b8 = s2 + ((rr & 1) ? G2_W7 : G2_W9) + (6 + 8 * (mat >> 1) + rr + (mat & 1)) * 16;
        const uint32_t bf = s2 + G2_P2 + (2 * rr + (mat & 1)) * 16;
        const uint32_t pg = sb + OFF_PG2 + ch * 6144;
        const int bfirst = role ? 1 : 3, blast = role ? 2 : 3;
#pragma unroll 1
        for (int b = bfirst; b <= blast; ++b) {
            const int T0 = 4 * b;
            float a8[4][2][4];
#pragma unroll
            for (int tj = 0; tj < 4; ++tj)
#pragma unroll
                for (int br = 0; br < 2; ++br) { a8[tj][br][0] = a8[tj][br][1] = a8[tj][br][2] = a8[tj][br][3] = 0.f; }
            if (b >= 2) {
                const uint32_t base = b8 + (T0 - 8) * 256;
#pragma unroll
                for (int loc = -7; loc <= 3; ++loc) {
                    if (T0 - 8 + loc >= 0) {
                        uint32_t fr[4];
                        ldsm4t(fr, base + loc * 256);
#pragma unroll
                        for (int tj = 0; tj < 4; ++tj) {
                            const int ks = tj - loc;
                            if (ks >= 0 && ks <= 7) {
                                mma_bf16(a8[tj][0], fr, k8[ks][0][0], k8[ks][0][1]);
                                mma_bf16(a8[tj][1], fr, k8[ks][1][0], k8[ks][1][1]);
                            }
                        }
                    }
                }
#pragma unroll
                for (int tj = 0; tj < 4; ++tj) {
                    uint32_t r0, r1;
                    ldsm2t(r0, r1, bf + (T0 - 8 + tj) * 256);
                    mma_bf16_k8(a8[tj][0], r0, r1, kf[0]);
                    mma_bf16_k8(a8[tj][1], r0, r1, kf[1]);
                }
            }
            float a4[4][2][4];
#pragma unroll
            for (int tj = 0; tj < 4; ++tj)
#pragma unroll
                for (int br = 0; br < 2; ++br) {
                    a4[tj][br][0] = a8[tj][br][0]; a4[tj][br][1] = a8[tj][br][2];
                    a4[tj][br][2] = a8[tj][br][1]; a4[tj][br][3] = a8[tj][br][3];
                }
            {
                const uint32_t base = b4 + (2 * T0 - 8) * 128;
#pragma unroll
                for (int loc = -8; loc <= 6; ++loc) {
                    if (2 * T0 - 8 + loc >= -2) {
                        uint32_t fr[4];
                        ldsm4t(fr, base + loc * 128);
#pragma unroll
                        for (int tj = 0; tj < 4; ++tj) {
                            const int ks = 2 * tj - loc;
                            if (ks >= 0 && ks <= 8) {
                                mma_bf16(a4[tj][0], fr, k4[ks][0][0], k4[ks][0][1]);
                                mma_bf16(a4[tj][1], fr, k4[ks][1][0], k4[ks][1][1]);
                            }
                        }
                    }
                }
            }
#pragma unroll
            for (int tj = 0; tj < 4; ++tj)
#pragma unroll
                for (int c = 0; c < 4; ++c) {
                    const int h = c >> 1, e = c & 1;
                    const int idx = 128 * (T0 - 4 + tj) + 64 * h + 16 * q + 8 * (e ^ (q >> 1)) + g;
                    sts32(pg + idx * 4, pack_bf16(a4[tj][0][c], a4[tj][1][c]));
                }
        }
    }
    STAMP(7);
    asm volatile("bar.sync 3, 256;\n" ::: "memory");
    STAMP(8);

    const uint32_t s1 = sb + OFF_SG1 + ch * SG1_CH;
    if (role == 0) {
        uint32_t kb[3][9][2][2];
        const uint32_t o1 = KT_WD1 + (g - 2 * q + 16) * 4;
#pragma unroll
        for (int p = 0; p < 3; ++p)
#pragma unroll
            for (int ks = 0; ks < 9; ++ks)
#pragma unroll
                for (int hh = 0; hh < 2; ++hh) {
                    kb[p][ks][0][hh] = lds32(ktA + o1 + p * 608 + (16 * ks - 8 * hh) * 4);
                    kb[p][ks][1][hh] = lds32(ktB + o1 + p * 608 + (16 * ks - 8 * hh) * 4);
                }
        const int lcb = 16 * rr + (mat & 1) + (mat >> 1);
#pragma unroll 1
        for (int gam = 0; gam < 4; ++gam) {
            uint32_t off[10];
#pragma unroll
            for (int li = 0; li < 10; ++li) { const int lc = lcb + 4 * gam + 2 * li; off[li] = s1 + (lc + (lc >> 4)) * 16; }
            float ae[2][2][4], ao[2][2][4];
            toep_pair<0>(ae, ae, kb[0], off, 0);
            toep_pair<1>(ao, ae, kb[1], off, ARR1);
            toep_pair<2>(ae, ae, kb[2], off, 2 * ARR1);
            const uint32_t dst = sb + OFF_S1P + gam * 8192 + ch * 2048;
#pragma unroll
            for (int tj = 0; tj < 2; ++tj)
#pragma unroll
                for (int h = 0; h < 2; ++h)
                    sts128(dst + (16 * g + 8 * tj + 4 * (h ^ (g & 1)) + q) * 16,
                           pack_bf16(ae[tj][0][2 * h], ae[tj][1][2 * h]), pack_bf16(ao[tj][0][2 * h], ao[tj][1][2 * h]),
                           pack_bf16(ae[tj][0][2 * h + 1], ae[tj][1][2 * h + 1]), pack_bf16(ao[tj][0][2 * h + 1], ao[tj][1][2 * h + 1]));
            __syncwarp();
            if (lane == 0) mbar_arrive(sb + OFF_MB_P + 8 * gam);
            STAMP(9 + gam);
        }
    } else {
        uint32_t kb[9][2][2];
        const uint32_t o2 = KT_WD2 + (np - q + 7) * 4;
#pragma unroll
        for (int ks = 0; ks < 9; ++ks)
#pragma unroll
            for (int hh = 0; hh < 2; ++hh) {
                kb[ks][0][hh] = lds32(ktA + o2 + (8 * ks - 4 * hh) * 4);
                kb[ks][1][hh] = lds32(ktB + o2 + (8 * ks - 4 * hh) * 4);
            }
        const int lcb = 16 * rr + (mat >> 1);
        const uint32_t zb = s1 + (3 + 2 * (mat & 1)) * ARR1;
        const int un = tid - 128, g2 = un >> 4, th = un & 15;
        const uint32_t su = (un ^ ((g2 & 1) << 2)) * 16;
        uint32_t oaddr, obar;
        asm("mapa.shared::cluster.u32 %0,%1,%2;\n" : "=r"(oaddr) : "r"(sb + OFF_OUT + (g2 >> 1) * 1024 + th * 16 + rank * 8), "r"(g2 & 1));
        asm("mapa.shared::cluster.u32 %0,%1,%2;\n" : "=r"(obar) : "r"(sb + OFF_MB_OUT), "r"(g2 & 1));
#pragma unroll 1
        for (int gam = 0; gam < 4; ++gam) {
            uint32_t off[10];
#pragma unroll
            for (int li = 0; li < 10; ++li) { const int lc = lcb + 4 * gam + 2 * li; off[li] = zb + (lc + (lc >> 4)) * 16; }
            float a0[2][2][4], a1[2][2][4];
            toep_pair<0>(a0, a0, kb, off, 0);
            toep_pair<0>(a1, a1, kb, off, ARR1);
            const uint32_t s2p = sb + OFF_S2P + (gam & 1) * 8192;
#pragma unroll
            for (int tj = 0; tj < 2; ++tj)
#pragma unroll
                for (int e = 0; e < 2; ++e)
                    sts128(s2p + ch * 2048 + (16 * g + 8 * tj + 4 * (e ^ (g & 1)) + q) * 16,
                           pack_bf16(a0[tj][0][e], a0[tj][1][e]), pack_bf16(a1[tj][0][e], a1[tj][1][e]),
                           pack_bf16(a0[tj][0][2 + e], a0[tj][1][2 + e]), pack_bf16(a1[tj][0][2 + e], a1[tj][1][2 + e]));
            __syncwarp();
            if (lane == 0) mbar_arrive(sb + OFF_MB_P + 8 * gam);
            if (gam == 0) mbar_wait(sb + OFF_MB_GT);
            mbar_wait(sb + OFF_MB_P + 8 * gam);
            const int tu = 64 * g2 + 16 * gam + th;
            const uint4 gw = lds128(sb + OFF_GT + tu * 16);
            const int up = tu - 128;
            const uint32_t pgo = sb + OFF_PG2 + (up ^ (((up >> 3) & 1) << 1)) * 16;
            uint4 pr[4];
#pragma unroll
            for (int c = 0; c < 4; ++c) {
                const uint4 x = lds128(sb + OFF_S1P + gam * 8192 + c * 2048 + su);
                const uint4 y = lds128(s2p + c * 2048 + su);
                uint4 s;
                s.x = badd2(x.x, y.x); s.y = badd2(x.y, y.y); s.z = badd2(x.z, y.z); s.w = badd2(x.w, y.w);
                if (g2 >= 2) {
                    const uint4 z = lds128(pgo + c * 6144);
                    s.x = badd2(s.x, z.x); s.y = badd2(s.y, z.y); s.z = badd2(s.z, z.z); s.w = badd2(s.w, z.w);
                }
                pr[c].x = bmul2(s.x, gw.x); pr[c].y = bmul2(s.y, gw.y); pr[c].z = bmul2(s.z, gw.z); pr[c].w = bmul2(s.w, gw.w);
            }
#define EMIT(F, K)                                                                                                   \
            {                                                                                                        \
                const uint32_t o0 = badd2(plo(pr[0].F, pr[1].F), phi(pr[0].F, pr[1].F));                             \
                const uint32_t o1 = badd2(plo(pr[2].F, pr[3].F), phi(pr[2].F, pr[3].F));                             \
                asm volatile("st.async.weak.shared::cluster.mbarrier::complete_tx::bytes.v2.b32 [%0],{%1,%2},[%3];\n" \
                             :: "r"(oaddr + gam * 4096 + (K) * 256), "r"(o0), "r"(o1), "r"(obar + 8 * gam) : "memory"); \
            }
            EMIT(x, 0) EMIT(y, 1) EMIT(z, 2) EMIT(w, 3)
#undef EMIT
            STAMP(9 + gam);
        }
    }
}

typedef CUresult (*EncodeFn)(CUtensorMap*, CUtensorMapDataType, cuuint32_t, void*, const cuuint64_t*, const cuuint64_t*,
                             const cuuint32_t*, const cuuint32_t*, CUtensorMapInterleave, CUtensorMapSwizzle,
                             CUtensorMapL2promotion, CUtensorMapFloatOOBfill);

}

extern "C" void kernel_launch(void* const* d_in, const int* in_sizes, int n_in, void* d_out, int out_size) {
    (void)in_sizes; (void)n_in; (void)out_size;
    static EncodeFn encode = nullptr;
    if (!encode) {
        void* fn = nullptr;
        cudaDriverEntryPointQueryResult qr;
        cudaGetDriverEntryPoint("cuTensorMapEncodeTiled", &fn, cudaEnableDefault, &qr);
        encode = (EncodeFn)fn;
        cudaFuncSetAttribute(fused_s4d_kernel, cudaFuncAttributeMaxDynamicSharedMemorySize, SMEM_BYTES);
    }
    CUtensorMap tin, tout;
    {
        cuuint64_t gd[3] = {DCH, 128, 16};
        cuuint64_t gs[2] = {16 * 1024, 1024};
        cuuint32_t bx[3] = {8, 128, 16};
        cuuint32_t es[3] = {1, 1, 1};
        encode(&tin, CU_TENSOR_MAP_DATA_TYPE_BFLOAT16, 3, d_in[0], gd, gs, bx, es, CU_TENSOR_MAP_INTERLEAVE_NONE,
               CU_TENSOR_MAP_SWIZZLE_NONE, CU_TENSOR_MAP_L2_PROMOTION_NONE, CU_TENSOR_MAP_FLOAT_OOB_FILL_NONE);
    }
    {
        cuuint64_t gd[4] = {DCH, 128, 4, 4};
        cuuint64_t gs[3] = {4096, 1024, 512 * 1024};
        cuuint32_t bx[4] = {8, 16, 4, 4};
        cuuint32_t es[4] = {1, 1, 1, 1};
        encode(&tout, CU_TENSOR_MAP_DATA_TYPE_BFLOAT16, 4, d_out, gd, gs, bx, es, CU_TENSOR_MAP_INTERLEAVE_NONE,
               CU_TENSOR_MAP_SWIZZLE_NONE, CU_TENSOR_MAP_L2_PROMOTION_NONE, CU_TENSOR_MAP_FLOAT_OOB_FILL_NONE);
    }
    Params prm;
    prm.u = (const __nv_bfloat16*)d_in[0];
    for (int j = 0; j < 6; ++j) {
        prm.p[0][j] = (const __nv_bfloat16*)d_in[1 + j];
        prm.p[1][j] = (const __nv_bfloat16*)d_in[8 + j];
    }
    prm.gw = (const __nv_bfloat16*)d_in[14];
    fused_s4d_kernel<<<128, NTHREADS, SMEM_BYTES, cudaStreamPerThread>>>(tin, tout, prm);
}
```

```cpp
#include <cuda_runtime.h>
#include <cuda_bf16.h>
#include <cuda_fp16.h>
#include <cuda.h>
#include <stdint.h>

#define PROFILE_CLK 0
#define WAKE 0
#define EXP 0

namespace {

constexpr int LSEQ = 2048;
constexpr int DCH = 512;
constexpr int NTHREADS = 384;

constexpr int OFF_U = 0;
constexpr int OFF_S2P = OFF_U;
constexpr int ARR1 = 154 * 16;
constexpr int SG1_CH = 7 * ARR1;
constexpr int G2_W5 = 0, G2_W3 = 3776, G2_W9 = 7552, G2_W7 = 9728, G2_P2 = 11904, SG2_CH = 13952;
constexpr int OFF_SG2 = 32768;
constexpr int OFF_SG1 = OFF_SG2 + 4 * SG2_CH;
constexpr int OFF_S1P = OFF_SG2;
constexpr int OFF_ROWS = OFF_SG2 + 32768;
constexpr int OFF_PG2 = OFF_SG1 + 4 * SG1_CH;
constexpr int OFF_GT = OFF_PG2 + 24576;
constexpr int KT_W = 2816;
constexpr int KT_WD1 = 0, KT_WD2 = KT_WD1 + 3 * 608, KT_FIX = KT_WD2 + 3 * 320;
constexpr int OFF_KT = OFF_PG2 + 35840;
constexpr int FT_W = 8 * 71 * 16;
constexpr int OFF_FT = OFF_KT - 8 * FT_W;
constexpr int OFF_OUT = OFF_KT + 8 * KT_W;
constexpr int OFF_MISC = OFF_OUT + 16384;
constexpr int OFF_MB_U = OFF_MISC, OFF_MB_P1 = OFF_MISC + 8, OFF_MB_P2 = OFF_MISC + 40, OFF_MB_OUT = OFF_MISC + 72;
constexpr int OFF_TAG = OFF_MISC + 104;
constexpr int OFF_GPART = OFF_OUT;
constexpr int SMEM_BYTES = OFF_MISC + 128;
static_assert(OFF_SG1 % 128 == 0 && OFF_KT % 128 == 0 && OFF_OUT % 128 == 0 && OFF_FT >= OFF_SG1, "align");
static_assert(KT_FIX + 4 <= KT_W, "kt");
static_assert(SMEM_BYTES <= 232448, "smem");

struct Params {
    const __nv_bfloat16* u;
    const __nv_bfloat16* p[2][6];
    const __nv_bfloat16* gw;
};

__device__ __align__(128) uint32_t g_gate[LSEQ];
__device__ uint32_t g_epoch;
__device__ uint32_t g_arrived;
#define STAMP(i) do {} while (0)
#define GSTAMP(i) do {} while (0)

__device__ __forceinline__ void ldsm4(uint32_t (&r)[4], uint32_t a) {
    asm volatile("ldmatrix.sync.aligned.m8n8.x4.shared.b16 {%0,%1,%2,%3},[%4];\n"
                 : "=r"(r[0]), "=r"(r[1]), "=r"(r[2]), "=r"(r[3]) : "r"(a) : "memory");
}
__device__ __forceinline__ void ldsm4t(uint32_t (&r)[4], uint32_t a) {
    asm volatile("ldmatrix.sync.aligned.m8n8.x4.trans.shared.b16 {%0,%1,%2,%3},[%4];\n"
                 : "=r"(r[0]), "=r"(r[1]), "=r"(r[2]), "=r"(r[3]) : "r"(a) : "memory");
}
__device__ __forceinline__ void ldsm2t(uint32_t& r0, uint32_t& r1, uint32_t a) {
    asm volatile("ldmatrix.sync.aligned.m8n8.x2.trans.shared.b16 {%0,%1},[%2];\n" : "=r"(r0), "=r"(r1) : "r"(a) : "memory");
}
__device__ __forceinline__ void mma_bf16(float (&d)[4], const uint32_t (&a)[4], uint32_t b0, uint32_t b1) {
    asm("mma.sync.aligned.m16n8k16.row.col.f32.bf16.bf16.f32 {%0,%1,%2,%3},{%4,%5,%6,%7},{%8,%9},{%0,%1,%2,%3};\n"
        : "+f"(d[0]), "+f"(d[1]), "+f"(d[2]), "+f"(d[3])
        : "r"(a[0]), "r"(a[1]), "r"(a[2]), "r"(a[3]), "r"(b0), "r"(b1));
}
__device__ __forceinline__ void mma_bf16_c(float (&d)[4], const uint32_t (&a)[4], uint32_t b0, uint32_t b1,
                                           float c0, float c1, float c2, float c3) {
    asm("mma.sync.aligned.m16n8k16.row.col.f32.bf16.bf16.f32 {%0,%1,%2,%3},{%4,%5,%6,%7},{%8,%9},{%10,%11,%12,%13};\n"
        : "=f"(d[0]), "=f"(d[1]), "=f"(d[2]), "=f"(d[3])
        : "r"(a[0]), "r"(a[1]), "r"(a[2]), "r"(a[3]), "r"(b0), "r"(b1), "f"(c0), "f"(c1), "f"(c2), "f"(c3));
}
__device__ __forceinline__ void mma_bf16_k8(float (&d)[4], uint32_t a0, uint32_t a1, uint32_t b0) {
    asm("mma.sync.aligned.m16n8k8.row.col.f32.bf16.bf16.f32 {%0,%1,%2,%3},{%4,%5},{%6},{%0,%1,%2,%3};\n"
        : "+f"(d[0]), "+f"(d[1]), "+f"(d[2]), "+f"(d[3]) : "r"(a0), "r"(a1), "r"(b0));
}
__device__ __forceinline__ void mma_f16(float (&d)[4], const uint32_t (&a)[4], uint32_t b0, uint32_t b1) {
    asm("mma.sync.aligned.m16n8k16.row.col.f32.f16.f16.f32 {%0,%1,%2,%3},{%4,%5,%6,%7},{%8,%9},{%0,%1,%2,%3};\n"
        : "+f"(d[0]), "+f"(d[1]), "+f"(d[2]), "+f"(d[3])
        : "r"(a[0]), "r"(a[1]), "r"(a[2]), "r"(a[3]), "r"(b0), "r"(b1));
}
__device__ __forceinline__ uint32_t lds32(uint32_t a) {
    uint32_t v; asm volatile("ld.shared.u32 %0,[%1];\n" : "=r"(v) : "r"(a) : "memory"); return v;
}
__device__ __forceinline__ uint4 lds128(uint32_t a) {
    uint4 v; asm volatile("ld.shared.v4.u32 {%0,%1,%2,%3},[%4];\n" : "=r"(v.x), "=r"(v.y), "=r"(v.z), "=r"(v.w) : "r"(a) : "memory");
    return v;
}
__device__ __forceinline__ void sts32(uint32_t a, uint32_t v) { asm volatile("st.shared.u32 [%0],%1;\n" :: "r"(a), "r"(v) : "memory"); }
__device__ __forceinline__ void sts128(uint32_t a, uint32_t x, uint32_t y, uint32_t z, uint32_t w) {
    asm volatile("st.shared.v4.u32 [%0],{%1,%2,%3,%4};\n" :: "r"(a), "r"(x), "r"(y), "r"(z), "r"(w) : "memory");
}
__device__ __forceinline__ uint32_t pack_bf16(float lo, float hi) {
    uint32_t r; asm("cvt.rn.bf16x2.f32 %0,%1,%2;\n" : "=r"(r) : "f"(hi), "f"(lo)); return r;
}
__device__ __forceinline__ uint32_t pack_f16(float lo, float hi) {
    uint32_t r; asm("cvt.rn.f16x2.f32 %0,%1,%2;\n" : "=r"(r) : "f"(hi), "f"(lo)); return r;
}
__device__ __forceinline__ uint32_t badd2(uint32_t a, uint32_t b) {
    uint32_t r; asm("add.rn.bf16x2 %0,%1,%2;\n" : "=r"(r) : "r"(a), "r"(b)); return r;
}
__device__ __forceinline__ uint32_t bmul2(uint32_t a, uint32_t b) {
    uint32_t r; asm("mul.rn.bf16x2 %0,%1,%2;\n" : "=r"(r) : "r"(a), "r"(b)); return r;
}
__device__ __forceinline__ void sts64(uint32_t a, uint32_t x, uint32_t y) {
    asm volatile("st.shared.v2.u32 [%0],{%1,%2};\n" :: "r"(a), "r"(x), "r"(y) : "memory");
}
__device__ __forceinline__ uint32_t gmix(uint32_t w0, uint32_t w1, uint32_t gw) {
    uint32_t r;
    asm("{.reg .b32 a,b,g,h,t; .reg .b16 l,u; prmt.b32 a,%1,%2,0x5410; prmt.b32 b,%1,%2,0x7632;\n"
        "mov.b32 {l,u},%3; mov.b32 g,{l,l}; mov.b32 h,{u,u}; mul.rn.bf16x2 t,b,h; fma.rn.bf16x2 %0,a,g,t;}\n"
        : "=r"(r) : "r"(w0), "r"(w1), "r"(gw));
    return r;
}
__device__ __forceinline__ uint32_t plo(uint32_t a, uint32_t b) { return __byte_perm(a, b, 0x5410); }
__device__ __forceinline__ uint32_t phi(uint32_t a, uint32_t b) { return __byte_perm(a, b, 0x7632); }
__device__ __forceinline__ float bf_lo(uint32_t v) { return __uint_as_float(v << 16); }
__device__ __forceinline__ float bf_hi(uint32_t v) { return __uint_as_float(v & 0xFFFF0000u); }
__device__ __forceinline__ float bf_round(float x) { return __bfloat162float(__float2bfloat16_rn(x)); }

__device__ __forceinline__ void mbar_init(uint32_t a, uint32_t cnt) {
    asm volatile("mbarrier.init.shared.b64 [%0],%1;\n" :: "r"(a), "r"(cnt) : "memory");
}
__device__ __forceinline__ void mbar_arrive(uint32_t a) {
    asm volatile("mbarrier.arrive.shared.b64 _,[%0];\n" :: "r"(a) : "memory");
}
__device__ __forceinline__ void mbar_expect(uint32_t a, uint32_t bytes) {
    asm volatile("mbarrier.arrive.expect_tx.shared.b64 _,[%0],%1;\n" :: "r"(a), "r"(bytes) : "memory");
}
__device__ __forceinline__ void mbar_wait(uint32_t a) {
    uint32_t ok = 0;
#pragma unroll 1
    for (int it = 0; it < (1 << 20) && !ok; ++it)
        asm volatile("{.reg .pred p; mbarrier.try_wait.parity.shared.b64 p,[%1],0; selp.u32 %0,1,0,p;}\n"
                     : "=r"(ok) : "r"(a) : "memory");
}
__device__ __forceinline__ void mbar_wait_cluster(uint32_t a) {
    uint32_t ok = 0;
#pragma unroll 1
    for (int it = 0; it < (1 << 20) && !ok; ++it)
        asm volatile("{.reg .pred p; mbarrier.try_wait.parity.acquire.cluster.shared.b64 p,[%1],0; selp.u32 %0,1,0,p;}\n"
                     : "=r"(ok) : "r"(a) : "memory");
}

struct c32 { float x, y; };
__device__ __forceinline__ c32 csq(c32 z) { c32 r; r.x = fmaf(z.x, z.x, -(z.y * z.y)); r.y = (z.x + z.x) * z.y; return r; }
__device__ __forceinline__ c32 cexp_seed(float al2, float ai, float x) {
    float m, s, c, th = ai * x, e = al2 * x;
    asm("ex2.approx.ftz.f32 %0,%1;\n" : "=f"(m) : "f"(e));
    asm("sin.approx.ftz.f32 %0,%1;\n" : "=f"(s) : "f"(th));
    asm("cos.approx.ftz.f32 %0,%1;\n" : "=f"(c) : "f"(th));
    c32 r; r.x = m * c; r.y = m * s; return r;
}
typedef unsigned long long pc;
__device__ __forceinline__ pc mk64(uint32_t re, uint32_t im) { pc r; asm("mov.b64 %0,{%1,%2};\n" : "=l"(r) : "r"(re), "r"(im)); return r; }
__device__ __forceinline__ pc mkp(c32 a, c32 b) {
    pc r;
    asm("{.reg .b32 x,y; cvt.rn.f16x2.f32 x,%2,%1; cvt.rn.f16x2.f32 y,%4,%3; mov.b64 %0,{x,y};}\n"
        : "=l"(r) : "f"(a.x), "f"(b.x), "f"(a.y), "f"(b.y));
    return r;
}
__device__ __forceinline__ pc pmul(pc z, pc w) {
    pc r;
    asm("{.reg .b32 zr,zi,wr,wi,t0,t1,n; mov.b64 {zr,zi},%1; mov.b64 {wr,wi},%2;\n"
        "mul.rn.f16x2 t0,zr,wr; mul.rn.f16x2 t1,zi,wr; neg.f16x2 n,zi;\n"
        "fma.rn.f16x2 t0,n,wi,t0; fma.rn.f16x2 t1,zr,wi,t1; mov.b64 %0,{t0,t1};}\n"
        : "=l"(r) : "l"(z), "l"(w));
    return r;
}
__device__ __forceinline__ void stp(uint32_t a, pc v) {
    asm volatile("{.reg .b32 x,y; mov.b64 {x,y},%1; stmatrix.sync.aligned.m8n8.x2.shared.b16 [%0],{x,y};}\n"
                 :: "r"(a), "l"(v) : "memory");
}
__device__ __forceinline__ void mma_f16p(float (&d)[4], const uint32_t (&a)[4], pc b) {
    asm("{.reg .b32 x,y; mov.b64 {x,y},%8;\n"
        "mma.sync.aligned.m16n8k16.row.col.f32.f16.f16.f32 {%0,%1,%2,%3},{%4,%5,%6,%7},{x,y},{%0,%1,%2,%3};}\n"
        : "+f"(d[0]), "+f"(d[1]), "+f"(d[2]), "+f"(d[3]) : "r"(a[0]), "r"(a[1]), "r"(a[2]), "r"(a[3]), "l"(b));
}

__device__ __forceinline__ void store_pair(uint32_t a0, uint32_t a1, uint32_t v0, uint32_t v1, uint32_t v2, uint32_t v3,
                                           uint32_t v4, uint32_t v5, uint32_t v6, uint32_t v7) {
    sts128(a0, plo(v0, v1), plo(v2, v3), plo(v4, v5), plo(v6, v7));
    sts128(a1, phi(v0, v1), phi(v2, v3), phi(v4, v5), phi(v6, v7));
}

constexpr int PD = 4, RS = 5;
template <int NP, int NK, bool FORK>
__device__ __forceinline__ void toep_group(float (&acc)[2][2][2][4], const uint32_t (&kb)[NK][9][2][2], uint32_t (&fr)[RS][4],
                                           uint32_t (&off)[10], uint32_t ynext) {
#pragma unroll
    for (int n = 0; n < NP * 10; ++n) {
        {
            const int m = n + PD;
            if (m < NP * 10) {
                ldsm4(fr[m % RS], off[m % 10] + (m / 10) * ARR1);
                if (m / 10 == NP - 1) off[m % 10] = (ynext + 34 * (m % 10)) & ~15u;
            } else {
                ldsm4(fr[m % RS], off[m - NP * 10]);
            }
        }
        const int p = n / 10, li = n % 10;
        const int ai = FORK ? (p == 1 ? 1 : 0) : p;
        const int kp = (NK == 1) ? 0 : p;
#pragma unroll
        for (int tj = 0; tj < 2; ++tj) {
            const int ks = tj + 8 - li;
            if (ks >= 0 && ks <= 8) {
#pragma unroll
                for (int br = 0; br < 2; ++br) {
                    if (ks == 8 && (p == 0 || !FORK))
                        mma_bf16_c(acc[ai][tj][br], fr[n % RS], kb[kp][ks][br][0], kb[kp][ks][br][1], 0.f, 0.f, 0.f, 0.f);
                    else if (ks == 8 && p == 1)
                        mma_bf16_c(acc[1][tj][br], fr[n % RS], kb[kp][ks][br][0], kb[kp][ks][br][1], acc[0][tj][br][0],
                                   acc[0][tj][br][1], acc[0][tj][br][2], acc[0][tj][br][3]);
                    else
                        mma_bf16(acc[ai][tj][br], fr[n % RS], kb[kp][ks][br][0], kb[kp][ks][br][1]);
                }
            }
        }
    }
}

template <int TS, int KMAX, int LO, int HI, int STRIDE>
__device__ __forceinline__ void toep_block(float (&acc)[4][2][4], const uint32_t (&kb)[KMAX + 1][2][2], uint32_t base,
                                           const uint32_t (&f0)[4], const uint32_t (&f1)[4]) {
    uint32_t fr[4][4];
#pragma unroll
    for (int j = 0; j < 4; ++j) { fr[0][j] = f0[j]; fr[1][j] = f1[j]; }
    if (LO + 2 <= HI) ldsm4t(fr[2], base + (uint32_t)((LO + 2) * STRIDE));
#pragma unroll
    for (int loc = LO; loc <= HI; ++loc) {
        if (loc + 3 <= HI) ldsm4t(fr[(loc + 3 - LO) & 3], base + (loc + 3) * STRIDE);
#pragma unroll
        for (int tj = 0; tj < 4; ++tj) {
            const int ks = TS * tj - loc;
            if (ks >= 0 && ks <= KMAX) {
                mma_bf16(acc[tj][0], fr[(loc - LO) & 3], kb[ks][0][0], kb[ks][0][1]);
                mma_bf16(acc[tj][1], fr[(loc - LO) & 3], kb[ks][1][0], kb[ks][1][1]);
            }
        }
    }
}

__device__ __forceinline__ uint32_t gate_word(float s) {
    float sb = bf_round(s);
    float g = bf_round(1.0f / (1.0f + expf(-sb)));
    float o = bf_round(1.0f - g);
    return ((__float_as_uint(g) >> 16) | (__float_as_uint(o) & 0xFFFF0000u)) & 0x7FFF7FFFu;
}

__global__ void __cluster_dims__(2, 1, 1) __launch_bounds__(NTHREADS, 1)
fused_s4d_kernel(const __grid_constant__ Params prm, const __grid_constant__ CUtensorMap tm_in,
                 const __grid_constant__ CUtensorMap tm_out) {
    extern __shared__ __align__(1024) unsigned char smem[];
    const uint32_t sb = (uint32_t)__cvta_generic_to_shared(smem);
    const int tid = threadIdx.x, warp = tid >> 5, lane = tid & 31;
    const int rank = blockIdx.x & 1, cl = blockIdx.x >> 1;
    if (warp != 8) asm volatile("barrier.cluster.arrive.relaxed.aligned;\n" ::: "memory");
    STAMP(0);
    if (tid == 128) GSTAMP(0);

    if (warp >= 8) {
        asm volatile("setmaxnreg.dec.sync.aligned.u32 120;\n");
        const int un = tid - 256;
        if (warp == 8) {
            if (lane == 0) {
                asm volatile("prefetch.tensormap [%0];\n" :: "l"(&tm_in) : "memory");
                asm volatile("prefetch.tensormap [%0];\n" :: "l"(&tm_out) : "memory");
                mbar_init(sb + OFF_MB_U, 1);
#pragma unroll
                for (int i = 0; i < 4; ++i) {
                    mbar_init(sb + OFF_MB_P1 + 8 * i, 4); mbar_init(sb + OFF_MB_P2 + 8 * i, 4); mbar_init(sb + OFF_MB_OUT + 8 * i, 1);
                }
                mbar_expect(sb + OFF_MB_U, 32768);
#pragma unroll
                for (int i = 0; i < 4; ++i) mbar_expect(sb + OFF_MB_OUT + 8 * i, 2048);
                asm volatile("fence.mbarrier_init.release.cluster;\n" ::: "memory");
                asm volatile("fence.proxy.async.shared::cta;\n" ::: "memory");
            }
            __syncwarp();
            asm volatile("barrier.cluster.arrive.relaxed.aligned;\n" ::: "memory");
        }
        asm volatile("barrier.cluster.wait.acquire.aligned;\n" ::: "memory");
        if (un == 0) {
            asm volatile("cp.async.bulk.tensor.3d.shared::cluster.global.mbarrier::complete_tx::bytes.multicast::cluster "
                         "[%0],[%1,{%2,%3,%4}],[%5],%6;\n"
                         :: "r"(sb + OFF_U + rank * 16384), "l"(&tm_in), "r"(8 * cl), "r"(0), "r"(8 * rank), "r"(sb + OFF_MB_U),
                            "h"((uint16_t)3) : "memory");
        }
        STAMP(9);
        {
            const uint32_t a2 = sb + OFF_SG2 + (warp - 8) * SG2_CH;
            sts128(a2 + (lane < 16 ? G2_W5 : G2_W3) + ((lane & 15) + ((lane >> 3) & 1)) * 16, 0, 0, 0, 0);
            if (lane < 16) sts128(a2 + (lane < 8 ? G2_W9 : G2_W7 - 128) + lane * 16, 0, 0, 0, 0);
        }
        STAMP(1);
        mbar_wait(sb + OFF_MB_U);
        STAMP(2);
        const int pi = lane >> 4;
#define LOAD_U()                                                                                             \
        const int pw = (warp - 8) + 4 * it, rho = pw * 16 + (lane & 15);                                      \
        const uint32_t ua = sb + OFF_U + rho * 16 + rank * 8 + pi * 4;                                        \
        uint32_t v[25];                                                          \
        _Pragma("unroll") for (int j = 0; j < 4; ++j) v[j] = (rho > 0) ? lds32(ua + (12 + j) * 2048 - 16) : 0u; \
        _Pragma("unroll") for (int j = 0; j < 16; ++j) v[4 + j] = lds32(ua + j * 2048);                       \
        _Pragma("unroll") for (int j = 0; j < 5; ++j) v[20 + j] = lds32(ua + j * 2048 + 16);
#pragma unroll 1
        for (int it = 0; it < 2; ++it) {
            if (it == 1) {
                STAMP(3);
                asm volatile("bar.arrive 2, 384;\n" ::: "memory");
        {
                const int g = lane >> 2, q = lane & 3;
        uint32_t epoch = 0;
        if (warp == 8) asm volatile("ld.relaxed.gpu.global.u32 %0,[%1];\n" : "=r"(epoch) : "l"(&g_epoch) : "memory");
        uint4 gx[8], gwv[4];
        {
            const uint4* ur = reinterpret_cast<const uint4*>(prm.u) + (size_t)(blockIdx.x * 16 + g) * 64 + (warp - 8) * 16 + q;
            const uint4* wr = reinterpret_cast<const uint4*>(prm.gw) + (warp - 8) * 16 + q;
#pragma unroll
            for (int j = 0; j < 4; ++j) { gx[2 * j] = __ldg(ur + 4 * j); gx[2 * j + 1] = __ldg(ur + 8 * 64 + 4 * j); gwv[j] = __ldg(wr + 4 * j); }
        }

        {
            float gs[4] = {0.f, 0.f, 0.f, 0.f}, gt[4] = {0.f, 0.f, 0.f, 0.f};
#pragma unroll
            for (int j = 0; j < 4; ++j) {
                uint32_t a[4], b[4];
                a[0] = bmul2(gx[2 * j].x, gwv[j].x); a[1] = bmul2(gx[2 * j + 1].x, gwv[j].x);
                a[2] = bmul2(gx[2 * j].y, gwv[j].y); a[3] = bmul2(gx[2 * j + 1].y, gwv[j].y);
                b[0] = bmul2(gx[2 * j].z, gwv[j].z); b[1] = bmul2(gx[2 * j + 1].z, gwv[j].z);
                b[2] = bmul2(gx[2 * j].w, gwv[j].w); b[3] = bmul2(gx[2 * j + 1].w, gwv[j].w);
                mma_bf16(gs, a, 0x3F803F80u, 0x3F803F80u);
                mma_bf16(gt, b, 0x3F803F80u, 0x3F803F80u);
            }
            if (q == 0) {
                sts32(sb + OFF_GPART + ((warp - 8) * 16 + g) * 4, __float_as_uint(gs[0] + gt[0]));
                sts32(sb + OFF_GPART + ((warp - 8) * 16 + g + 8) * 4, __float_as_uint(gs[2] + gt[2]));
            }
        }
        asm volatile("bar.sync 1, 128;\n" ::: "memory");
        if (warp == 8) {
            const uint32_t tg = (epoch + 1u) & 3u;
            if (lane < 16) {
                float s = 0.f;
#pragma unroll
                for (int w = 0; w < 4; ++w) s += __uint_as_float(lds32(sb + OFF_GPART + (w * 16 + lane) * 4));
                const uint32_t wd = gate_word(s) | ((tg & 1u) << 15) | ((tg & 2u) << 30);
                asm volatile("st.relaxed.gpu.global.u32 [%0],%1;\n" :: "l"(&g_gate[blockIdx.x * 16 + lane]), "r"(wd) : "memory");
            }
            if (lane == 0) {
                sts32(sb + OFF_TAG, ((tg & 1u) << 15) | ((tg & 2u) << 30));
                sts32(sb + OFF_TAG + 4, epoch + 1u);
            }
        }
        }
                STAMP(10);
                if (warp >= 10) break;
            }
            LOAD_U();
            uint32_t p2[23], w3[24], p4[20], w5[22];
#pragma unroll
            for (int j = 0; j < 23; ++j) p2[j] = badd2(v[j], v[j + 1]);
#pragma unroll
            for (int j = 4; j < 24; ++j) w3[j] = badd2(p2[j - 1], v[j + 1]);
#pragma unroll
            for (int j = 0; j < 20; ++j) p4[j] = badd2(p2[j], p2[j + 2]);
#pragma unroll
            for (int j = 4; j < 22; ++j) w5[j] = badd2(p4[j - 2], v[j + 2]);
            const uint32_t s2a = sb + OFF_SG2 + (2 * pi) * SG2_CH;
            const int c5 = 2 * rho + 16;
            const uint32_t a5 = s2a + G2_W5 + (c5 + (c5 >> 3)) * 16, a3 = a5 + (G2_W3 - G2_W5);
            store_pair(a5, a5 + SG2_CH, w5[4], w5[5], w5[6], w5[7], w5[8], w5[9], w5[10], w5[11]);
            store_pair(a5 + 16, a5 + 16 + SG2_CH, w5[12], w5[13], w5[14], w5[15], w5[16], w5[17], w5[18], w5[19]);
            store_pair(a3, a3 + SG2_CH, w3[8], w3[9], w3[10], w3[11], w3[12], w3[13], w3[14], w3[15]);
            store_pair(a3 + 16, a3 + 16 + SG2_CH, w3[16], w3[17], w3[18], w3[19], w3[20], w3[21], w3[22], w3[23]);
            if (it == 0) {
                uint32_t w7[20], w9[20];
#pragma unroll
                for (int j = 4; j < 20; ++j) { w7[j] = badd2(p4[j - 3], w3[j + 2]); w9[j] = badd2(p4[j - 4], w5[j + 2]); }
                const uint32_t a9 = s2a + G2_W9 + (2 * rho + 8) * 16, a7 = s2a + G2_W7 + (2 * rho + 8) * 16;
                const uint32_t ap = s2a + G2_P2 + (2 * rho) * 16;
                store_pair(a9, a9 + SG2_CH, w9[4], w9[5], w9[6], w9[7], w9[8], w9[9], w9[10], w9[11]);
                store_pair(a9 + 16, a9 + 16 + SG2_CH, w9[12], w9[13], w9[14], w9[15], w9[16], w9[17], w9[18], w9[19]);
                store_pair(a7, a7 + SG2_CH, w7[4], w7[5], w7[6], w7[7], w7[8], w7[9], w7[10], w7[11]);
                store_pair(a7 + 16, a7 + 16 + SG2_CH, w7[12], w7[13], w7[14], w7[15], w7[16], w7[17], w7[18], w7[19]);
                store_pair(ap, ap + SG2_CH, p2[0], p2[1], p2[2], p2[3], p2[4], p2[5], p2[6], p2[7]);
                store_pair(ap + 16, ap + 16 + SG2_CH, p2[8], p2[9], p2[10], p2[11], p2[12], p2[13], p2[14], p2[15]);
                if (rho == 0) {
                    const uint32_t n1 = v[4], n2 = p2[4], n3 = w3[5], n4 = p4[4];
                    store_pair(a5 - 32, a5 - 32 + SG2_CH, 0, 0, 0, 0, 0, 0, n1, n2);
                    store_pair(a3 - 32, a3 - 32 + SG2_CH, 0, 0, 0, n1, w3[4], w3[5], w3[6], w3[7]);
                    store_pair(a9 - 16, a9 - 16 + SG2_CH, 0, 0, 0, 0, n1, n2, n3, n4);
                    store_pair(a7 - 16, a7 - 16 + SG2_CH, 0, 0, 0, 0, 0, n1, n2, n3);
                }
            }
        }
        asm volatile("bar.arrive 4, 256;\n" ::: "memory");
        asm volatile("bar.sync 7, 384;\n" ::: "memory");
        {
            const uint32_t a1 = sb + OFF_SG1 + (warp - 8) * SG1_CH;
            if (lane < 17) {
                const uint32_t o = (lane < 16 ? lane : 153) * 16;
                sts128(a1 + o, 0, 0, 0, 0); sts128(a1 + ARR1 + o, 0, 0, 0, 0); sts128(a1 + 2 * ARR1 + o, 0, 0, 0, 0);
            }
            const uint32_t o = (lane + (lane >> 4)) * 16;
            sts128(a1 + 3 * ARR1 + o, 0, 0, 0, 0); sts128(a1 + 4 * ARR1 + o, 0, 0, 0, 0);
            if (lane < 31) { sts128(a1 + 5 * ARR1 + o, 0, 0, 0, 0); sts128(a1 + 6 * ARR1 + o, 0, 0, 0, 0); }
        }
#pragma unroll 1
        for (int it = 0; it < 2; ++it) {
            LOAD_U();
            uint32_t p2[19];
#pragma unroll
            for (int j = 3; j < 19; ++j) p2[j] = badd2(v[j], v[j + 1]);
            const uint32_t s1a = sb + OFF_SG1 + (2 * pi) * SG1_CH;
            {
                const int lc = rho + 16;
                const uint32_t a = s1a + (lc + (lc >> 4)) * 16;
                store_pair(a, a + SG1_CH, p2[4], p2[6], p2[8], p2[10], p2[12], p2[14], p2[16], p2[18]);
                store_pair(a + ARR1, a + ARR1 + SG1_CH, v[4], v[6], v[8], v[10], v[12], v[14], v[16], v[18]);
                store_pair(a + 2 * ARR1, a + 2 * ARR1 + SG1_CH, v[5], v[7], v[9], v[11], v[13], v[15], v[17], v[19]);
            }
            if (pw < 7) {
                uint32_t w3[20];
#pragma unroll
                for (int j = 4; j < 20; ++j) w3[j] = badd2(p2[j - 1], v[j + 1]);
                const int lc = rho + 32;
                const uint32_t a = s1a + 3 * ARR1 + (lc + (lc >> 4)) * 16;
#pragma unroll
                for (int ph = 0; ph < 4; ++ph)
                    store_pair(a + ph * ARR1, a + ph * ARR1 + SG1_CH, w3[4 + ph], v[6 + ph], w3[8 + ph], v[10 + ph],
                               w3[12 + ph], v[14 + ph], w3[16 + ph], v[18 + ph]);
                if (rho == 0) {
                    const uint32_t az = s1a + 5 * ARR1 + 32 * 16;
                    store_pair(az, az + SG1_CH, 0, 0, 0, 0, 0, 0, 0, v[4]);
                    store_pair(az + ARR1, az + ARR1 + SG1_CH, 0, 0, 0, 0, 0, 0, v[4], v[5]);
                }
            }
        }
#undef LOAD_U
        asm volatile("bar.arrive 3, 256;\n" ::: "memory");
        asm volatile("bar.arrive 5, 256;\n" ::: "memory");
        STAMP(4);
        if (EXP == 6) return;
        asm volatile("bar.sync 1, 128;\n" ::: "memory");
        {
            const uint32_t tagw = lds32(sb + OFF_TAG);
            bool done = false;
#pragma unroll 1
            for (int tries = 0; tries < 8192 && !done; ++tries) {
                uint4 v[4];
#pragma unroll
                for (int i = 0; i < 4; ++i)
                    asm volatile("ld.relaxed.gpu.global.v4.u32 {%0,%1,%2,%3},[%4];\n"
                                 : "=r"(v[i].x), "=r"(v[i].y), "=r"(v[i].z), "=r"(v[i].w)
                                 : "l"(&g_gate[(i * 128 + un) * 4]) : "memory");
                uint32_t bad = 0;
#pragma unroll
                for (int i = 0; i < 4; ++i)
                    bad |= (v[i].x ^ tagw) | (v[i].y ^ tagw) | (v[i].z ^ tagw) | (v[i].w ^ tagw);
                done = __all_sync(0xffffffffu, (bad & 0x80008000u) == 0);
                if (done) {
#pragma unroll
                    for (int i = 0; i < 4; ++i)
                        sts128(sb + OFF_GT + (i * 128 + un) * 16, v[i].x & 0x7FFF7FFFu, v[i].y & 0x7FFF7FFFu,
                               v[i].z & 0x7FFF7FFFu, v[i].w & 0x7FFF7FFFu);
                } else {
                    __nanosleep(64);
                }
            }
            if (!done) {
#pragma unroll 1
                for (int k = 0; k < 512; ++k) {
                    const int t = (k >> 7) * 512 + (warp - 8) * 128 + (k & 127);
                    float s = 0.f;
#pragma unroll 1
                    for (int j = 0; j < 8; ++j) {
                        const uint32_t pr = bmul2(reinterpret_cast<const uint32_t*>(prm.u)[t * 256 + j * 32 + lane],
                                                  reinterpret_cast<const uint32_t*>(prm.gw)[j * 32 + lane]);
                        s += bf_lo(pr) + bf_hi(pr);
                    }
#pragma unroll
                    for (int o = 16; o > 0; o >>= 1) s += __shfl_xor_sync(0xffffffffu, s, o);
                    if (lane == 0) sts32(sb + OFF_GT + t * 4, gate_word(s));
                }
            }
        }
        asm volatile("bar.sync 1, 128;\n" ::: "memory");
        STAMP(11);
        if (un == 32) {
                asm volatile("{.reg .pred p; .reg .u32 n;\n"
                             "atom.relaxed.gpu.global.inc.u32 n,[%0],%2;\n"
                             "setp.eq.u32 p,n,%2;\n"
                             "@p st.relaxed.gpu.global.u32 [%1],%3;}\n"
                             :: "l"(&g_arrived), "l"(&g_epoch), "r"(gridDim.x - 1), "r"(lds32(sb + OFF_TAG + 4)) : "memory");
        }
        __syncwarp();
        if (EXP == 5) return;
        const int g2 = un >> 4, th = un & 15;
        const uint32_t su = (un ^ ((g2 & 1) << 2)) * 16;
        uint32_t oaddr, obar;
        asm("mapa.shared::cluster.u32 %0,%1,%2;\n" : "=r"(oaddr) : "r"(sb + OFF_OUT + un * 16), "r"(rank ^ 1));
        asm("mapa.shared::cluster.u32 %0,%1,%2;\n" : "=r"(obar) : "r"(sb + OFF_MB_OUT), "r"(rank ^ 1));
        const uint32_t orow = sb + OFF_ROWS + g2 * 512 + th * 16;
        uint4 pr[4], gw;
        const uint32_t zst = g2 >= 2 ? 6144u : 0u;
#define FINAL_PRE(G)                                                                                         \
        {                                                                                                     \
            const int tu = 64 * g2 + 16 * (G) + th, up = tu - 128;                                            \
            gw = lds128(sb + OFF_GT + tu * 16);                                                               \
            const uint32_t pgo = g2 >= 2 ? sb + OFF_PG2 + (up ^ (((up >> 3) & 1) << 1)) * 16 : sb + OFF_KT;   \
            _Pragma("unroll") for (int c = 0; c < 4; ++c) pr[c] = lds128(pgo + c * zst);                      \
        }
        mbar_wait(sb + OFF_MB_P2);
        mbar_wait(sb + OFF_MB_P1);
        FINAL_PRE(0);
#pragma unroll 1
        for (int gam = 0; gam < 4; ++gam) {
            mbar_wait(sb + OFF_MB_P2 + 8 * gam);
#pragma unroll
            for (int c = 0; c < 4; ++c) {
                const uint4 y = lds128(sb + OFF_S2P + gam * 8192 + c * 2048 + su);
                pr[c].x = badd2(pr[c].x, y.x); pr[c].y = badd2(pr[c].y, y.y); pr[c].z = badd2(pr[c].z, y.z); pr[c].w = badd2(pr[c].w, y.w);
            }
            mbar_wait(sb + OFF_MB_P1 + 8 * gam);
            if (EXP == 11 && gam == 2) STAMP(0);
#pragma unroll
            for (int c = 0; c < 4; ++c) {
                const uint4 x = lds128(sb + OFF_S1P + gam * 8192 + c * 2048 + su);
                pr[c].x = badd2(pr[c].x, x.x); pr[c].y = badd2(pr[c].y, x.y); pr[c].z = badd2(pr[c].z, x.z); pr[c].w = badd2(pr[c].w, x.w);
            }
            const uint32_t r00 = gmix(pr[0].x, pr[1].x, gw.x), r01 = gmix(pr[2].x, pr[3].x, gw.x);
            const uint32_t r10 = gmix(pr[0].y, pr[1].y, gw.y), r11 = gmix(pr[2].y, pr[3].y, gw.y);
            const uint32_t r20 = gmix(pr[0].z, pr[1].z, gw.z), r21 = gmix(pr[2].z, pr[3].z, gw.z);
            const uint32_t r30 = gmix(pr[0].w, pr[1].w, gw.w), r31 = gmix(pr[2].w, pr[3].w, gw.w);
            asm volatile("st.async.weak.shared::cluster.mbarrier::complete_tx::bytes.v4.b32 [%0],{%1,%2,%3,%4},[%5];\n"
                         :: "r"(oaddr + gam * 2048), "r"(rank ? r00 : r20), "r"(rank ? r01 : r21), "r"(rank ? r10 : r30),
                            "r"(rank ? r11 : r31), "r"(obar + 8 * gam) : "memory");
            const uint32_t m0 = rank ? r20 : r00, m1 = rank ? r21 : r01, m2 = rank ? r30 : r10, m3 = rank ? r31 : r11;
            STAMP(5 + gam);
            FINAL_PRE((gam + 1) & 3);
            if (EXP == 11 && gam == 2) STAMP(1);
            mbar_wait_cluster(sb + OFF_MB_OUT + 8 * gam);
            if (EXP == 11 && gam == 2) STAMP(2);
            const uint4 pe = lds128(sb + OFF_OUT + gam * 2048 + un * 16);
            sts64(orow + gam * 4096 + rank * 8, m0, m1); sts64(orow + gam * 4096 + 256 + rank * 8, m2, m3);
            sts64(orow + gam * 4096 + 8 - rank * 8, pe.x, pe.y); sts64(orow + gam * 4096 + 264 - rank * 8, pe.z, pe.w);
            if (EXP == 11 && gam == 2) STAMP(3);
            asm volatile("fence.proxy.async.shared::cta;\n" ::: "memory");
            if (EXP == 11 && gam == 2) STAMP(4);
            asm volatile("bar.sync 1, 128;\n" ::: "memory");
            if (EXP == 11 && gam == 2) { __syncwarp(); STAMP(9); }
            if (un == 0) {
                asm volatile("cp.async.bulk.tensor.4d.global.shared::cta.bulk_group [%0,{%1,%2,%3,%4}],[%5];\n"
                             :: "l"(&tm_out), "r"(8 * cl), "r"(16 * gam), "r"(2 * rank), "r"(0),
                                "r"(sb + OFF_ROWS + gam * 4096) : "memory");
                asm volatile("cp.async.bulk.commit_group;\n" ::: "memory");
            }
            if (gam == 3) STAMP(12);
        }
#undef FINAL_PRE
        if (un == 0) {
            asm volatile("cp.async.bulk.wait_group.read 0;\n" ::: "memory");
            STAMP(13);
            GSTAMP(1);
        }
        return;
    }

    const int ch = warp & 3, role = warp >> 2;
    const int chg = 8 * cl + 4 * rank + ch;
    const int g = lane >> 2, q = lane & 3;

    uint2 pLA, pAI, pCR, pCI;
    {
        const size_t o = (size_t)chg * 128 + lane * 4;
        pLA = __ldg(reinterpret_cast<const uint2*>(prm.p[role][0] + o));
        pAI = __ldg(reinterpret_cast<const uint2*>(prm.p[role][1] + o));
        pCR = __ldg(reinterpret_cast<const uint2*>(prm.p[role][2] + o));
        pCI = __ldg(reinterpret_cast<const uint2*>(prm.p[role][3] + o));
    }
    const float log_dt = __bfloat162float(prm.p[role][4][chg]);
    const float dskip = __bfloat162float(prm.p[role][5][chg]);

    const uint32_t kt = sb + OFF_KT + warp * KT_W;
    {
        const uint32_t z1 = kt + KT_WD1 + (lane < 16 ? lane : 130 + lane) * 4;
        if (lane < 22) { sts32(z1, 0u); sts32(z1 + 608, 0u); sts32(z1 + 1216, 0u); }
        const uint32_t z2 = kt + KT_WD2 + (lane < 7 ? lane : 64 + lane) * 4;
        if (lane < 16) { sts32(z2, 0u); sts32(z2 + 320, 0u); sts32(z2 + 640, 0u); }
    }
    float dt = 0.f, fscale = 0.f, cinv = 0.f, f0 = 0.f;
    float dk[5][4];
#pragma unroll
    for (int j = 0; j < 5; ++j) { dk[j][0] = dk[j][1] = dk[j][2] = dk[j][3] = 0.f; }
    {
        const uint32_t tb = sb + OFF_FT + warp * FT_W;
        const int mat = lane >> 3, rr = lane & 7;
        const uint32_t stb = tb + (71 * rr + 8 * (mat & 1)) * 16, stc = tb + (71 * rr + 64 + (mat & 1)) * 16;
        const uint32_t ld0 = tb + ((mat & 1) ? 64 + (mat >> 1) : 8 * (mat >> 1) + rr) * 16;
        const uint32_t ld1 = tb + (16 + 8 * mat + rr) * 16;
        const uint32_t ld2 = tb + ((mat & 2) ? 64 + mat : 48 + 8 * mat + rr) * 16;
        const uint32_t ld3 = tb + (71 * (mat >> 1) + 68 + (mat & 1)) * 16;
#pragma unroll
        for (int r = 0; r < 2; ++r) {
            uint32_t wLA = 0u, wAI = 0u, wCR = 0u, wCI = 0u;
            if (r == 0) {
                dt = bf_round(expf(log_dt));
                uint32_t m = max(max(max(pCR.x & 0x7F80u, (pCR.x >> 16) & 0x7F80u), max(pCR.y & 0x7F80u, (pCR.y >> 16) & 0x7F80u)),
                                 max(max(pCI.x & 0x7F80u, (pCI.x >> 16) & 0x7F80u), max(pCI.y & 0x7F80u, (pCI.y >> 16) & 0x7F80u)));
                m = __reduce_max_sync(0xffffffffu, m) >> 7;
                m = min(max(m, 1u), 253u);
                cinv = __uint_as_float((254u - m) << 23);
                fscale = 2.0f * dt * __uint_as_float(m << 23);
                wLA = pLA.x; wAI = pAI.x; wCR = pCR.x; wCI = pCI.x;
                STAMP(1);
            } else if (r == 1) {
                f0 = (bf_lo(pCR.x) + bf_hi(pCR.x)) + (bf_lo(pCR.y) + bf_hi(pCR.y));
#pragma unroll
                for (int o = 16; o > 0; o >>= 1) f0 += __shfl_xor_sync(0xffffffffu, f0, o);
                f0 = fmaf(2.0f * dt, f0, dskip);
                wLA = pLA.y; wAI = pAI.y; wCR = pCR.y; wCI = pCI.y;
            }
            float ea, eb;
            asm("ex2.approx.ftz.f32 %0,%1;\n" : "=f"(ea) : "f"(bf_lo(wLA) * 1.4426950408889634f));
            asm("ex2.approx.ftz.f32 %0,%1;\n" : "=f"(eb) : "f"(bf_hi(wLA) * 1.4426950408889634f));
            const uint32_t e2 = pack_bf16(ea, eb);
            const float ala = (-bf_lo(e2) * dt) * 1.4426950408889634f, alb = (-bf_hi(e2) * dt) * 1.4426950408889634f;
            const float aia = bf_lo(wAI) * dt, aib = bf_hi(wAI) * dt;
            const pc C = mk64(pack_f16(bf_lo(wCR) * cinv, bf_hi(wCR) * cinv), pack_f16(bf_lo(wCI) * cinv, bf_hi(wCI) * cinv));
            {
                c32 a = cexp_seed(ala, -aia, 16.f), b = cexp_seed(alb, -aib, 16.f);
                const pc f1 = mkp(a, b); a = csq(a); b = csq(b);
                const pc f2 = mkp(a, b); a = csq(a); b = csq(b);
                const pc f4 = mkp(a, b); a = csq(a); b = csq(b);
                stp(stb, 0x3C003C00ull);
                stp(stb + 16, f1); stp(stb + 32, f2); stp(stb + 64, f4); stp(stc, mkp(a, b));
                const pc f3 = pmul(f1, f2);
                stp(stb + 48, f3); stp(stb + 80, pmul(f1, f4)); stp(stb + 96, pmul(f2, f4)); stp(stb + 112, pmul(f3, f4));
                a = cexp_seed(ala, aia, 1.f); b = cexp_seed(alb, aib, 1.f);
                const pc w1 = mkp(a, b); a = csq(a); b = csq(b);
                const pc w2 = mkp(a, b); a = csq(a); b = csq(b);
                const pc w4 = mkp(a, b); a = csq(a); b = csq(b);
                const pc w8 = mkp(a, b);
                stp(stc + 32, w1);
                pc D[4];
                D[0] = pmul(C, w1); D[1] = pmul(D[0], w2); D[2] = pmul(D[0], w4); D[3] = pmul(D[1], w4);
#pragma unroll
                for (int j = 0; j < 4; ++j) { stp(stb + 256 + 16 * j, D[j]); stp(stb + 320 + 16 * j, pmul(D[j], w8)); }
                a = cexp_seed(ala, aia, 256.f); b = cexp_seed(alb, aib, 256.f);
                const pc w256 = mkp(a, b); a = csq(a); b = csq(b);
                const pc w512 = mkp(a, b); a = csq(a); b = csq(b);
                const pc w1024 = mkp(a, b);
                stp(stc + 64, w256);
                D[0] = pmul(C, w4); D[1] = pmul(C, w8); D[2] = pmul(D[0], w8); D[3] = pmul(D[1], w8);
#pragma unroll
                for (int j = 0; j < 4; ++j) {
                    const pc t = pmul(D[j], w512);
                    stp(stb + 512 + 16 * j, t); stp(stb + 576 + 16 * j, pmul(t, w256));
                }
#pragma unroll
                for (int j = 0; j < 2; ++j) {
                    const pc t = pmul(D[2 * j + 1], w1024), t2 = pmul(t, w256);
                    stp(stb + 768 + 16 * j, t); stp(stb + 800 + 16 * j, t2);
                    stp(stb + 832 + 16 * j, pmul(t, w512)); stp(stb + 864 + 16 * j, pmul(t2, w512));
                }
            }
            __syncwarp();
#pragma unroll
            for (int s = 0; s < 8; s += 2) {
                uint32_t W[4];
                ldsm4(W, ld3 + s * 1136);
#pragma unroll
                for (int h = 0; h < 2; ++h) {
                    uint32_t L0[4], L1[4], L2[4];
                    ldsm4(L0, ld0 + (s + h) * 1136); ldsm4(L1, ld1 + (s + h) * 1136); ldsm4(L2, ld2 + (s + h) * 1136);
                    uint32_t A[4];
                    A[0] = L0[0]; A[2] = L0[2];
                    asm("{.reg .b32 t0,t1,n; mul.rn.f16x2 t0,%2,%4; mul.rn.f16x2 t1,%3,%4; neg.f16x2 n,%3;\n"
                        "fma.rn.f16x2 %0,n,%5,t0; fma.rn.f16x2 %1,%2,%5,t1;}\n"
                        : "=r"(A[1]), "=r"(A[3]) : "r"(L0[0]), "r"(L0[2]), "r"(L0[1]), "r"(L0[3]));
                    const pc t1 = pmul(mk64(L1[0], L1[1]), mk64(L2[2], L2[3]));
                    const pc t2 = pmul(t1, mk64(W[2 * h], W[2 * h + 1]));
                    mma_f16(dk[0], A, L1[0], L1[1]);
                    mma_f16(dk[3], A, L1[2], L1[3]);
                    mma_f16(dk[4], A, L2[0], L2[1]);
                    mma_f16p(dk[1], A, t1);
                    mma_f16p(dk[2], A, t2);
                }
            }
            __syncwarp();
        }
    }
    asm volatile("bar.arrive 7, 384;\n" ::: "memory");
    STAMP(2);

    {
        const bool last = (lane == 31);
#pragma unroll
        for (int j = 0; j < 5; ++j)
#pragma unroll
            for (int c = 0; c < 4; ++c) dk[j][c] *= fscale;
        const float f256 = dk[1][3], f512 = dk[2][3], f1024 = dk[3][3];
        if (last) { dk[0][3] -= f256; dk[1][3] = 0.f; dk[2][2] -= f512; dk[2][3] = 0.f; }
#pragma unroll
        for (int hh = 0; hh < 2; ++hh) {
            const int i = g + 8 * hh;
            sts32(kt + KT_WD2 + (4 * i + q + 8) * 4, pack_bf16(dk[2][2 * hh + 1], dk[2][2 * hh]));
            sts32(kt + KT_WD2 + 320 + (2 * i + (q & 1) + 32 * (q >> 1) + 8) * 4, pack_bf16(dk[3][2 * hh + 1], dk[3][2 * hh]));
            sts32(kt + KT_WD2 + 640 + (i + 16 * q + 7) * 4, pack_bf16(dk[4][2 * hh + 1], dk[4][2 * hh]));
        }
        if (last) {
            sts32(kt + KT_WD2 + 7 * 4, pack_bf16(f256, 0.f));
            sts32(kt + KT_WD2 + 320 + 7 * 4, pack_bf16(f512, 0.f));
            sts32(kt + KT_FIX, pack_bf16(f1024, f1024));
        }
        const float n0 = __shfl_sync(0xffffffffu, dk[0][0], (lane + 1) & 31), n1 = __shfl_sync(0xffffffffu, dk[0][2], (lane + 1) & 31);
        uint32_t ev[2][3];
#pragma unroll
        for (int hh = 0; hh < 2; ++hh) {
            const float a = dk[0][2 * hh], b = dk[1][2 * hh], c = dk[0][2 * hh + 1], d = dk[1][2 * hh + 1];
            const float an = hh == 0 ? (last ? n1 : n0) : (last ? 0.f : n1);
            ev[hh][0] = pack_bf16(d, b);
            ev[hh][1] = pack_bf16(an - d, c - b);
            ev[hh][2] = pack_bf16(c - d, a - b);
        }
        const uint32_t w0[3] = {pack_bf16(f0, 0.f), pack_bf16(dk[0][0] - f0, 0.f), pack_bf16(-f0, 0.f)};
#pragma unroll
        for (int p = 0; p < 3; ++p) {
            const uint32_t s0 = __shfl_sync(0xffffffffu, ev[0][p], (lane + 31) & 31), s1 = __shfl_sync(0xffffffffu, ev[1][p], (lane + 31) & 31);
            const uint32_t pv0 = lane == 0 ? w0[p] : s0, pv1 = lane == 0 ? s0 : s1;
            const uint32_t wa = kt + KT_WD1 + p * 608 + (2 * lane + 17) * 4;
            sts32(wa, __byte_perm(ev[0][p], pv0, 0x5432)); sts32(wa + 4, ev[0][p]);
            sts32(wa + 256, __byte_perm(ev[1][p], pv1, 0x5432)); sts32(wa + 260, ev[1][p]);
            if (lane == 0) sts32(wa - 4, w0[p]);
            if (last) sts32(wa + 264, ev[1][p] << 16);
        }
    }
    STAMP(3);

    const uint32_t ktA = sb + OFF_KT + ch * KT_W, ktB = ktA + 4 * KT_W;
    const int mat = lane >> 3, rr = lane & 7;
    const int np = 4 * (g & 1) + (g >> 1);

    {
        uint32_t k4[9][2][2], k8[8][2][2], kf[2];
        const uint32_t o4 = KT_WD2 + 320 + (g - q + 7) * 4;
        const uint32_t o8 = KT_WD2 + 640 + (np + 7 - q) * 4;
        const uint32_t s2 = sb + OFF_SG2 + ch * SG2_CH;
        const uint32_t b4 = s2 + ((rr & 1) ? G2_W3 : G2_W5) + (18 + 9 * (mat & 1) + 4 * (mat >> 1) + (rr >> 1)) * 16;
        const uint32_t b8 = s2 + ((rr & 1) ? G2_W7 : G2_W9) + (6 + 8 * (mat >> 1) + rr + (mat & 1)) * 16;
        const uint32_t bf = s2 + G2_P2 + (2 * rr + (mat & 1)) * 16;
        const uint32_t pg = sb + OFF_PG2 + ch * 6144 + (16 * q + g) * 4;
        const uint32_t pe0 = (q >> 1) * 32, pe1 = 32 - pe0;
        const int blk = 2 + role;
        const uint32_t c8 = b8 + (4 * blk - 8) * 256, c4 = b4 + (8 * blk - 8) * 144;
#define G2_STORE(ACC, BLK)                                                                                   \
        _Pragma("unroll") for (int tj = 0; tj < 4; ++tj) {                                                   \
            const uint32_t d = pg + ((BLK) - 1) * 2048 + tj * 512;                                           \
            sts32(d + pe0, pack_bf16(ACC[tj][0][0], ACC[tj][1][0]));                                         \
            sts32(d + pe1, pack_bf16(ACC[tj][0][1], ACC[tj][1][1]));                                         \
            sts32(d + 256 + pe0, pack_bf16(ACC[tj][0][2], ACC[tj][1][2]));                                   \
            sts32(d + 256 + pe1, pack_bf16(ACC[tj][0][3], ACC[tj][1][3]));                                   \
        }
#define K_LOAD(DST, OFF, KS)                                                                                 \
        { DST[KS][0][0] = lds32(ktA + OFF + (8 * (KS)) * 4); DST[KS][0][1] = lds32(ktA + OFF + (8 * (KS) - 4) * 4); \
          DST[KS][1][0] = lds32(ktB + OFF + (8 * (KS)) * 4); DST[KS][1][1] = lds32(ktB + OFF + (8 * (KS) - 4) * 4); }
        uint32_t fa[4], fb[4], fc[4], fx[4][2];
        asm volatile("bar.sync %0, 64;\n" :: "r"(8 + ch) : "memory");
        {
            const uint32_t msk = ((np >> 1) == q) ? ((np & 1) ? 0xFFFF0000u : 0x0000FFFFu) : 0u;
            kf[0] = lds32(ktA + KT_FIX) & msk; kf[1] = lds32(ktB + KT_FIX) & msk;
        }
#pragma unroll
        for (int ks = 0; ks < 4; ++ks) K_LOAD(k8, o8, ks);
        asm volatile("barrier.cluster.wait.acquire.aligned;\n" ::: "memory");
        asm volatile("bar.sync 2, 384;\n" ::: "memory");
        STAMP(6);
#pragma unroll
        for (int tj = 0; tj < 4; ++tj) ldsm2t(fx[tj][0], fx[tj][1], bf + (4 * blk - 8 + tj) * 256);
        ldsm4t(fa, c8); ldsm4t(fb, c8 + 256);
        float a8[4][2][4];
#pragma unroll
        for (int tj = 0; tj < 4; ++tj)
#pragma unroll
            for (int br = 0; br < 2; ++br) {
                a8[tj][br][0] = a8[tj][br][1] = a8[tj][br][2] = a8[tj][br][3] = 0.f;
                mma_bf16_k8(a8[tj][br], fx[tj][0], fx[tj][1], kf[br]);
            }
        {
            uint32_t fd[4];
            ldsm4t(fc, c8 + 512); ldsm4t(fd, c8 + 768);
#pragma unroll
            for (int ks = 8; ks >= 0; --ks) K_LOAD(k4, o4, ks);
#pragma unroll
            for (int loc = 0; loc < 4; ++loc)
#pragma unroll
                for (int tj = 3; tj >= loc; --tj) {
                    const uint32_t (&f)[4] = loc == 0 ? fa : loc == 1 ? fb : loc == 2 ? fc : fd;
                    mma_bf16(a8[tj][0], f, k8[tj - loc][0][0], k8[tj - loc][0][1]);
                    mma_bf16(a8[tj][1], f, k8[tj - loc][1][0], k8[tj - loc][1][1]);
                }
        }
        STAMP(5);
        if (role) {
            ldsm4t(fa, b4 - 2 * 144); ldsm4t(fb, b4 - 144);
#pragma unroll
            for (int ks = 4; ks < 8; ++ks) K_LOAD(k8, o8, ks);
            uint32_t fe[4], ff[4];
            ldsm4t(fe, b8); ldsm4t(ff, b8 + 256);
            float a1[4][2][4];
#pragma unroll
            for (int tj = 0; tj < 4; ++tj)
#pragma unroll
                for (int br = 0; br < 2; ++br) { a1[tj][br][0] = a1[tj][br][1] = a1[tj][br][2] = a1[tj][br][3] = 0.f; }
            toep_block<2, 8, -2, 6, 144>(a1, k4, b4, fa, fb);
            toep_block<1, 7, -4, -1, 256>(a8, k8, b8 + 4 * 256, fe, ff);
            G2_STORE(a1, 1);
            STAMP(4);
            asm volatile("bar.sync 4, 256;\n" ::: "memory");
        }
        ldsm4t(fa, c4 - 8 * 144); ldsm4t(fb, c4 - 7 * 144);
        float a4[4][2][4];
#pragma unroll
        for (int tj = 0; tj < 4; ++tj)
#pragma unroll
            for (int br = 0; br < 2; ++br) {
                a4[tj][br][0] = a8[tj][br][0]; a4[tj][br][1] = a8[tj][br][2];
                a4[tj][br][2] = a8[tj][br][1]; a4[tj][br][3] = a8[tj][br][3];
            }
        toep_block<2, 8, -8, 6, 144>(a4, k4, c4, fa, fb);
        G2_STORE(a4, blk);
#undef G2_STORE
#undef K_LOAD
    }
    STAMP(7);

    const uint32_t s1 = sb + OFF_SG1 + ch * SG1_CH;
    const uint32_t pu = (16 * g + q) * 16 + ch * 2048, px = (g & 1) * 64;
    if (role) {
        asm volatile("bar.arrive 6, 256;\n" ::: "memory");
        uint32_t kb[1][9][2][2];
        const uint32_t o2 = KT_WD2 + (np - q + 7) * 4;
#pragma unroll
        for (int ks = 0; ks < 9; ++ks)
#pragma unroll
            for (int hh = 0; hh < 2; ++hh) {
                kb[0][ks][0][hh] = lds32(ktA + o2 + (8 * ks - 4 * hh) * 4);
                kb[0][ks][1][hh] = lds32(ktB + o2 + (8 * ks - 4 * hh) * 4);
            }
        const uint32_t y0 = s1 + (3 + 2 * (mat & 1)) * ARR1 + 17 * (16 * rr + (mat >> 1));
        uint32_t off[10], fr[RS][4];
#pragma unroll
        for (int li = 0; li < 10; ++li) off[li] = (y0 + 34 * li) & ~15u;
        asm volatile("bar.sync 5, 256;\n" ::: "memory");
        STAMP(8);
#pragma unroll
        for (int n = 0; n < PD; ++n) ldsm4(fr[n], off[n]);
#pragma unroll 1
        for (int gam = 0; gam < 4; ++gam) {
            float acc[2][2][2][4];
            toep_group<2, 1, false>(acc, kb, fr, off, y0 + 68 * gam + 68);
            const uint32_t dst = sb + OFF_S2P + gam * 8192 + pu;
#pragma unroll
            for (int tj = 0; tj < 2; ++tj)
#pragma unroll
                for (int e = 0; e < 2; ++e)
                    sts128(dst + tj * 128 + (e ? 64 - px : px),
                           pack_bf16(acc[0][tj][0][e], acc[0][tj][1][e]), pack_bf16(acc[1][tj][0][e], acc[1][tj][1][e]),
                           pack_bf16(acc[0][tj][0][2 + e], acc[0][tj][1][2 + e]), pack_bf16(acc[1][tj][0][2 + e], acc[1][tj][1][2 + e]));
            __syncwarp();
            if (lane == 0) mbar_arrive(sb + OFF_MB_P2 + 8 * gam);
            STAMP(9 + gam);
        }
    } else {
        asm volatile("setmaxnreg.inc.sync.aligned.u32 216;\n");
        uint32_t kb[3][9][2][2];
        const uint32_t o1 = KT_WD1 + (g - 2 * q + 16) * 4;
#pragma unroll
        for (int p = 0; p < 3; ++p)
#pragma unroll
            for (int ks = 0; ks < 9; ++ks)
#pragma unroll
                for (int hh = 0; hh < 2; ++hh) {
                    kb[p][ks][0][hh] = lds32(ktA + o1 + p * 608 + (16 * ks - 8 * hh) * 4);
                    kb[p][ks][1][hh] = lds32(ktB + o1 + p * 608 + (16 * ks - 8 * hh) * 4);
                }
        const uint32_t y0 = s1 + 17 * (16 * rr + (mat & 1) + (mat >> 1));
        uint32_t off[10], fr[RS][4];
#pragma unroll
        for (int li = 0; li < 10; ++li) off[li] = (y0 + 34 * li) & ~15u;
        asm volatile("bar.sync 3, 256;\n" ::: "memory");
        STAMP(8);
#pragma unroll
        for (int n = 0; n < PD; ++n) ldsm4(fr[n], off[n]);
#pragma unroll 1
        for (int gam = 0; gam < 4; ++gam) {
            float acc[2][2][2][4];
            toep_group<3, 3, true>(acc, kb, fr, off, y0 + 68 * gam + 68);
            if (gam == 0) asm volatile("bar.sync 6, 256;\n" ::: "memory");
            const uint32_t dst = sb + OFF_S1P + gam * 8192 + pu;
#pragma unroll
            for (int tj = 0; tj < 2; ++tj)
#pragma unroll
                for (int h = 0; h < 2; ++h)
                    sts128(dst + tj * 128 + (h ? 64 - px : px),
                           pack_bf16(acc[0][tj][0][2 * h], acc[0][tj][1][2 * h]), pack_bf16(acc[1][tj][0][2 * h], acc[1][tj][1][2 * h]),
                           pack_bf16(acc[0][tj][0][2 * h + 1], acc[0][tj][1][2 * h + 1]),
                           pack_bf16(acc[1][tj][0][2 * h + 1], acc[1][tj][1][2 * h + 1]));
            __syncwarp();
            if (lane == 0) mbar_arrive(sb + OFF_MB_P1 + 8 * gam);
            STAMP(9 + gam);
        }
    }
}

typedef CUresult (*EncodeFn)(CUtensorMap*, CUtensorMapDataType, cuuint32_t, void*, const cuuint64_t*, const cuuint64_t*,
                             const cuuint32_t*, const cuuint32_t*, CUtensorMapInterleave, CUtensorMapSwizzle,
                             CUtensorMapL2promotion, CUtensorMapFloatOOBfill);

}

extern "C" void kernel_launch(void* const* d_in, const int* in_sizes, int n_in, void* d_out, int out_size) {
    (void)in_sizes; (void)n_in; (void)out_size;
    static EncodeFn encode = nullptr;
    if (!encode) {
        void* fn = nullptr;
        cudaDriverEntryPointQueryResult qr;
        cudaGetDriverEntryPoint("cuTensorMapEncodeTiled", &fn, cudaEnableDefault, &qr);
        encode = (EncodeFn)fn;
        cudaFuncSetAttribute(fused_s4d_kernel, cudaFuncAttributeMaxDynamicSharedMemorySize, SMEM_BYTES);
    }
    CUtensorMap tin, tout;
    {
        cuuint64_t gd[3] = {DCH, 128, 16};
        cuuint64_t gs[2] = {16 * 1024, 1024};
        cuuint32_t bx[3] = {8, 128, 8};
        cuuint32_t es[3] = {1, 1, 1};
        encode(&tin, CU_TENSOR_MAP_DATA_TYPE_BFLOAT16, 3, d_in[0], gd, gs, bx, es, CU_TENSOR_MAP_INTERLEAVE_NONE,
               CU_TENSOR_MAP_SWIZZLE_NONE, CU_TENSOR_MAP_L2_PROMOTION_NONE, CU_TENSOR_MAP_FLOAT_OOB_FILL_NONE);
    }
    {
        cuuint64_t gd[4] = {DCH, 64, 4, 8};
        cuuint64_t gs[3] = {4096, 1024, 256 * 1024};
        cuuint32_t bx[4] = {8, 16, 2, 8};
        cuuint32_t es[4] = {1, 1, 1, 1};
        encode(&tout, CU_TENSOR_MAP_DATA_TYPE_BFLOAT16, 4, d_out, gd, gs, bx, es, CU_TENSOR_MAP_INTERLEAVE_NONE,
               CU_TENSOR_MAP_SWIZZLE_NONE, CU_TENSOR_MAP_L2_PROMOTION_NONE, CU_TENSOR_MAP_FLOAT_OOB_FILL_NONE);
    }
    Params prm;
    prm.u = (const __nv_bfloat16*)d_in[0];
    for (int j = 0; j < 6; ++j) {
        prm.p[0][j] = (const __nv_bfloat16*)d_in[1 + j];
        prm.p[1][j] = (const __nv_bfloat16*)d_in[8 + j];
    }
    prm.gw = (const __nv_bfloat16*)d_in[14];
    fused_s4d_kernel<<<128, NTHREADS, SMEM_BYTES, cudaStreamPerThread>>>(prm, tin, tout);
}
```

```cpp
#include <cuda_runtime.h>
#include <cuda_bf16.h>
#include <cuda_fp16.h>
#include <cuda.h>
#include <stdint.h>

#define PROFILE_CLK 0
#define GDELAY 0
#define A_SPLIT 0
#define EXP 0

namespace {

constexpr int LSEQ = 2048;
constexpr int DCH = 512;
constexpr int NTHREADS = 384;

constexpr int OFF_U = 0;
constexpr int OFF_ROWS = OFF_U;
constexpr int G2_W5 = 0, G2_W3 = 3776, G2_W9E = 7552, G2_W9O = G2_W9E + 1152, G2_W7E = G2_W9O + 1152 + 48,
              G2_W7O = G2_W7E + 1152 + 16, G2_P2E = G2_W7O + 1088 + 64, G2_P2O = G2_P2E + 1024, SG2_CH = 14336;
static_assert((G2_W7O - G2_W9E) % 128 == 64 && (G2_W7E + 16 - G2_W9O) % 128 == 64 && G2_P2O + 1024 <= SG2_CH, "banks");
constexpr int OFF_SG2 = 32768;
constexpr int V_H = 144 * 16, V_CH = 2 * V_H;
constexpr int OFF_V = OFF_SG2 + 4 * SG2_CH;
constexpr int OFF_S1P = OFF_V + 4 * V_CH;
constexpr int OFF_PG2 = OFF_S1P + 32768;
constexpr int OFF_GT = OFF_PG2 + 24576;
constexpr int FT_W = 8 * 71 * 16;
constexpr int OFF_FT = OFF_S1P;
constexpr int KT_W = 2960;
constexpr int KT_WD1 = 0, KT_WD4 = 288 * 8, KT_FIX = KT_WD4 + 2 * 320;
constexpr int OFF_KT = OFF_FT + 8 * FT_W;
constexpr int OFF_OUT = OFF_KT + 8 * KT_W;
constexpr int OFF_MISC = OFF_OUT + 8192;
constexpr int OFF_MB_U = OFF_MISC, OFF_MB_P = OFF_MISC + 8, OFF_MB_OUT = OFF_MISC + 40;
constexpr int OFF_TAG = OFF_MISC + 72;
constexpr int OFF_ZERO = OFF_MISC + 96;
constexpr int OFF_GPART = OFF_MISC + 128;
constexpr int SMEM_BYTES = OFF_GPART + 256;
static_assert(OFF_V % 128 == 0 && OFF_S1P % 128 == 0 && OFF_KT % 128 == 0 && OFF_OUT % 128 == 0, "align");
static_assert(OFF_GT + 8192 <= OFF_KT && KT_FIX + 4 <= KT_W && SMEM_BYTES <= 232448, "smem");

struct Params {
    const __nv_bfloat16* u;
    const __nv_bfloat16* p[2][6];
    const __nv_bfloat16* gw;
};

__device__ __align__(128) uint32_t g_gate[LSEQ];
__device__ uint32_t g_epoch;
__device__ uint32_t g_arrived;
#define STAMP(i) do {} while (0)
#define GSTAMP(i) do {} while (0)

__device__ __forceinline__ void ldsm4(uint32_t (&r)[4], uint32_t a) {
    asm volatile("ldmatrix.sync.aligned.m8n8.x4.shared.b16 {%0,%1,%2,%3},[%4];\n"
                 : "=r"(r[0]), "=r"(r[1]), "=r"(r[2]), "=r"(r[3]) : "r"(a) : "memory");
}
__device__ __forceinline__ void ldsm4t(uint32_t (&r)[4], uint32_t a) {
    asm volatile("ldmatrix.sync.aligned.m8n8.x4.trans.shared.b16 {%0,%1,%2,%3},[%4];\n"
                 : "=r"(r[0]), "=r"(r[1]), "=r"(r[2]), "=r"(r[3]) : "r"(a) : "memory");
}
__device__ __forceinline__ void ldsm2t(uint32_t& r0, uint32_t& r1, uint32_t a) {
    asm volatile("ldmatrix.sync.aligned.m8n8.x2.trans.shared.b16 {%0,%1},[%2];\n" : "=r"(r0), "=r"(r1) : "r"(a) : "memory");
}
__device__ __forceinline__ void mma_bf16(float (&d)[4], const uint32_t (&a)[4], uint32_t b0, uint32_t b1) {
    asm("mma.sync.aligned.m16n8k16.row.col.f32.bf16.bf16.f32 {%0,%1,%2,%3},{%4,%5,%6,%7},{%8,%9},{%0,%1,%2,%3};\n"
        : "+f"(d[0]), "+f"(d[1]), "+f"(d[2]), "+f"(d[3])
        : "r"(a[0]), "r"(a[1]), "r"(a[2]), "r"(a[3]), "r"(b0), "r"(b1));
}
__device__ __forceinline__ void mma_bf16_k8(float (&d)[4], uint32_t a0, uint32_t a1, uint32_t b0) {
    asm("mma.sync.aligned.m16n8k8.row.col.f32.bf16.bf16.f32 {%0,%1,%2,%3},{%4,%5},{%6},{%0,%1,%2,%3};\n"
        : "+f"(d[0]), "+f"(d[1]), "+f"(d[2]), "+f"(d[3]) : "r"(a0), "r"(a1), "r"(b0));
}
__device__ __forceinline__ void mma_f16(float (&d)[4], const uint32_t (&a)[4], uint32_t b0, uint32_t b1) {
    asm("mma.sync.aligned.m16n8k16.row.col.f32.f16.f16.f32 {%0,%1,%2,%3},{%4,%5,%6,%7},{%8,%9},{%0,%1,%2,%3};\n"
        : "+f"(d[0]), "+f"(d[1]), "+f"(d[2]), "+f"(d[3])
        : "r"(a[0]), "r"(a[1]), "r"(a[2]), "r"(a[3]), "r"(b0), "r"(b1));
}
__device__ __forceinline__ uint32_t lds32(uint32_t a) {
    uint32_t v; asm volatile("ld.shared.u32 %0,[%1];\n" : "=r"(v) : "r"(a) : "memory"); return v;
}
__device__ __forceinline__ uint4 lds128(uint32_t a) {
    uint4 v; asm volatile("ld.shared.v4.u32 {%0,%1,%2,%3},[%4];\n" : "=r"(v.x), "=r"(v.y), "=r"(v.z), "=r"(v.w) : "r"(a) : "memory");
    return v;
}
__device__ __forceinline__ void sts32(uint32_t a, uint32_t v) { asm volatile("st.shared.u32 [%0],%1;\n" :: "r"(a), "r"(v) : "memory"); }
__device__ __forceinline__ void sts128(uint32_t a, uint32_t x, uint32_t y, uint32_t z, uint32_t w) {
    asm volatile("st.shared.v4.u32 [%0],{%1,%2,%3,%4};\n" :: "r"(a), "r"(x), "r"(y), "r"(z), "r"(w) : "memory");
}
__device__ __forceinline__ uint32_t pack_bf16(float lo, float hi) {
    uint32_t r; asm("cvt.rn.bf16x2.f32 %0,%1,%2;\n" : "=r"(r) : "f"(hi), "f"(lo)); return r;
}
__device__ __forceinline__ uint32_t pack_f16(float lo, float hi) {
    uint32_t r; asm("cvt.rn.f16x2.f32 %0,%1,%2;\n" : "=r"(r) : "f"(hi), "f"(lo)); return r;
}
__device__ __forceinline__ uint32_t badd2(uint32_t a, uint32_t b) {
    uint32_t r; asm("add.rn.bf16x2 %0,%1,%2;\n" : "=r"(r) : "r"(a), "r"(b)); return r;
}
__device__ __forceinline__ uint32_t bmul2(uint32_t a, uint32_t b) {
    uint32_t r; asm("mul.rn.bf16x2 %0,%1,%2;\n" : "=r"(r) : "r"(a), "r"(b)); return r;
}
__device__ __forceinline__ void sts64(uint32_t a, uint32_t x, uint32_t y) {
    asm volatile("st.shared.v2.u32 [%0],{%1,%2};\n" :: "r"(a), "r"(x), "r"(y) : "memory");
}
__device__ __forceinline__ uint2 lds64(uint32_t a) {
    uint2 v; asm volatile("ld.shared.v2.u32 {%0,%1},[%2];\n" : "=r"(v.x), "=r"(v.y) : "r"(a) : "memory"); return v;
}
__device__ __forceinline__ uint32_t bfma2(uint32_t a, uint32_t b, uint32_t c) {
    uint32_t r; asm("fma.rn.bf16x2 %0,%1,%2,%3;\n" : "=r"(r) : "r"(a), "r"(b), "r"(c)); return r;
}
__device__ __forceinline__ uint32_t plo(uint32_t a, uint32_t b) { return __byte_perm(a, b, 0x5410); }
__device__ __forceinline__ uint32_t phi(uint32_t a, uint32_t b) { return __byte_perm(a, b, 0x7632); }
__device__ __forceinline__ float bf_lo(uint32_t v) { return __uint_as_float(v << 16); }
__device__ __forceinline__ float bf_hi(uint32_t v) { return __uint_as_float(v & 0xFFFF0000u); }
__device__ __forceinline__ float bf_round(float x) { return __bfloat162float(__float2bfloat16_rn(x)); }

__device__ __forceinline__ void mbar_init(uint32_t a, uint32_t cnt) {
    asm volatile("mbarrier.init.shared.b64 [%0],%1;\n" :: "r"(a), "r"(cnt) : "memory");
}
__device__ __forceinline__ void mbar_arrive(uint32_t a) {
    asm volatile("mbarrier.arrive.shared.b64 _,[%0];\n" :: "r"(a) : "memory");
}
__device__ __forceinline__ void mbar_expect(uint32_t a, uint32_t bytes) {
    asm volatile("mbarrier.arrive.expect_tx.shared.b64 _,[%0],%1;\n" :: "r"(a), "r"(bytes) : "memory");
}
__device__ __forceinline__ void mbar_wait(uint32_t a) {
    uint32_t ok = 0;
#pragma unroll 1
    for (int it = 0; it < (1 << 20) && !ok; ++it)
        asm volatile("{.reg .pred p; mbarrier.try_wait.parity.shared.b64 p,[%1],0; selp.u32 %0,1,0,p;}\n"
                     : "=r"(ok) : "r"(a) : "memory");
}
__device__ __forceinline__ void mbar_wait_cluster(uint32_t a) {
    uint32_t ok = 0;
#pragma unroll 1
    for (int it = 0; it < (1 << 20) && !ok; ++it)
        asm volatile("{.reg .pred p; mbarrier.try_wait.parity.acquire.cluster.shared.b64 p,[%1],0; selp.u32 %0,1,0,p;}\n"
                     : "=r"(ok) : "r"(a) : "memory");
}

struct c32 { float x, y; };
__device__ __forceinline__ c32 csq(c32 z) { c32 r; r.x = fmaf(z.x, z.x, -(z.y * z.y)); r.y = (z.x + z.x) * z.y; return r; }
__device__ __forceinline__ c32 cexp_seed(float al2, float ai, float x) {
    float m, s, c, th = ai * x, e = al2 * x;
    asm("ex2.approx.ftz.f32 %0,%1;\n" : "=f"(m) : "f"(e));
    asm("sin.approx.ftz.f32 %0,%1;\n" : "=f"(s) : "f"(th));
    asm("cos.approx.ftz.f32 %0,%1;\n" : "=f"(c) : "f"(th));
    c32 r; r.x = m * c; r.y = m * s; return r;
}
typedef unsigned long long pc;
__device__ __forceinline__ pc mk64(uint32_t re, uint32_t im) { pc r; asm("mov.b64 %0,{%1,%2};\n" : "=l"(r) : "r"(re), "r"(im)); return r; }
__device__ __forceinline__ pc mkp(c32 a, c32 b) {
    pc r;
    asm("{.reg .b32 x,y; cvt.rn.f16x2.f32 x,%2,%1; cvt.rn.f16x2.f32 y,%4,%3; mov.b64 %0,{x,y};}\n"
        : "=l"(r) : "f"(a.x), "f"(b.x), "f"(a.y), "f"(b.y));
    return r;
}
__device__ __forceinline__ pc pmul(pc z, pc w) {
    pc r;
    asm("{.reg .b32 zr,zi,wr,wi,t0,t1,n; mov.b64 {zr,zi},%1; mov.b64 {wr,wi},%2;\n"
        "mul.rn.f16x2 t0,zr,wr; mul.rn.f16x2 t1,zi,wr; neg.f16x2 n,zi;\n"
        "fma.rn.f16x2 t0,n,wi,t0; fma.rn.f16x2 t1,zr,wi,t1; mov.b64 %0,{t0,t1};}\n"
        : "=l"(r) : "l"(z), "l"(w));
    return r;
}
__device__ __forceinline__ void stp(uint32_t a, pc v) {
    asm volatile("{.reg .b32 x,y; mov.b64 {x,y},%1; stmatrix.sync.aligned.m8n8.x2.shared.b16 [%0],{x,y};}\n"
                 :: "r"(a), "l"(v) : "memory");
}
__device__ __forceinline__ void mma_f16p(float (&d)[4], const uint32_t (&a)[4], pc b) {
    asm("{.reg .b32 x,y; mov.b64 {x,y},%8;\n"
        "mma.sync.aligned.m16n8k16.row.col.f32.f16.f16.f32 {%0,%1,%2,%3},{%4,%5,%6,%7},{x,y},{%0,%1,%2,%3};}\n"
        : "+f"(d[0]), "+f"(d[1]), "+f"(d[2]), "+f"(d[3]) : "r"(a[0]), "r"(a[1]), "r"(a[2]), "r"(a[3]), "l"(b));
}

__device__ __forceinline__ void store_pair(uint32_t a0, uint32_t a1, uint32_t v0, uint32_t v1, uint32_t v2, uint32_t v3,
                                           uint32_t v4, uint32_t v5, uint32_t v6, uint32_t v7) {
    sts128(a0, plo(v0, v1), plo(v2, v3), plo(v4, v5), plo(v6, v7));
    sts128(a1, phi(v0, v1), phi(v2, v3), phi(v4, v5), phi(v6, v7));
}

__device__ __forceinline__ void wgmma_n128(float (&d)[64], uint32_t a0, uint32_t a1, uint32_t a2, uint32_t a3, uint32_t dlo,
                                           int accumulate) {
    asm volatile("{.reg .pred p; .reg .b64 ds; setp.ne.s32 p,%69,0; mov.b64 ds,{%68,%70};\n"
                 "wgmma.mma_async.sync.aligned.m64n128k16.f32.bf16.bf16 {%0,%1,%2,%3,%4,%5,%6,%7,%8,%9,%10,%11,%12,%13,%14,%15,%16,%17,%18,%19,%20,%21,%22,%23,%24,%25,%26,%27,%28,%29,%30,%31,%32,%33,%34,%35,%36,%37,%38,%39,%40,%41,%42,%43,%44,%45,%46,%47,%48,%49,%50,%51,%52,%53,%54,%55,%56,%57,%58,%59,%60,%61,%62,%63},\n"
                 "{%64,%65,%66,%67},ds,p,1,1,0;}\n"
                 : "+f"(d[0]),"+f"(d[1]),"+f"(d[2]),"+f"(d[3]),"+f"(d[4]),"+f"(d[5]),"+f"(d[6]),"+f"(d[7]),"+f"(d[8]),"+f"(d[9]),"+f"(d[10]),"+f"(d[11]),"+f"(d[12]),"+f"(d[13]),"+f"(d[14]),"+f"(d[15]),"+f"(d[16]),"+f"(d[17]),"+f"(d[18]),"+f"(d[19]),"+f"(d[20]),"+f"(d[21]),"+f"(d[22]),"+f"(d[23]),"+f"(d[24]),"+f"(d[25]),"+f"(d[26]),"+f"(d[27]),"+f"(d[28]),"+f"(d[29]),"+f"(d[30]),"+f"(d[31]),"+f"(d[32]),"+f"(d[33]),"+f"(d[34]),"+f"(d[35]),"+f"(d[36]),"+f"(d[37]),"+f"(d[38]),"+f"(d[39]),"+f"(d[40]),"+f"(d[41]),"+f"(d[42]),"+f"(d[43]),"+f"(d[44]),"+f"(d[45]),"+f"(d[46]),"+f"(d[47]),"+f"(d[48]),"+f"(d[49]),"+f"(d[50]),"+f"(d[51]),"+f"(d[52]),"+f"(d[53]),"+f"(d[54]),"+f"(d[55]),"+f"(d[56]),"+f"(d[57]),"+f"(d[58]),"+f"(d[59]),"+f"(d[60]),"+f"(d[61]),"+f"(d[62]),"+f"(d[63])
                 : "r"(a0), "r"(a1), "r"(a2), "r"(a3), "r"(dlo), "r"(accumulate), "n"(128 >> 4));
}

template <int TS, int KMAX, int LO, int HI, int STRIDE>
__device__ __forceinline__ void toep_block(float (&acc)[4][2][4], const uint32_t (&kb)[KMAX + 1][2][2], uint32_t base,
                                           const uint32_t (&f0)[4], const uint32_t (&f1)[4]) {
    uint32_t fr[4][4];
#pragma unroll
    for (int j = 0; j < 4; ++j) { fr[0][j] = f0[j]; fr[1][j] = f1[j]; }
    if (LO + 2 <= HI) ldsm4t(fr[2], base + (uint32_t)((LO + 2) * STRIDE));
#pragma unroll
    for (int loc = LO; loc <= HI; ++loc) {
        if (loc + 3 <= HI) ldsm4t(fr[(loc + 3 - LO) & 3], base + (loc + 3) * STRIDE);
#pragma unroll
        for (int tj = 0; tj < 4; ++tj) {
            const int ks = TS * tj - loc;
            if (ks >= 0 && ks <= KMAX) {
                mma_bf16(acc[tj][0], fr[(loc - LO) & 3], kb[ks][0][0], kb[ks][0][1]);
                mma_bf16(acc[tj][1], fr[(loc - LO) & 3], kb[ks][1][0], kb[ks][1][1]);
            }
        }
    }
}

__device__ __forceinline__ uint32_t gate_word(float s) {
    float sb = bf_round(s);
    float g = bf_round(1.0f / (1.0f + expf(-sb)));
    float o = bf_round(1.0f - g);
    return ((__float_as_uint(g) >> 16) | (__float_as_uint(o) & 0xFFFF0000u)) & 0x7FFF7FFFu;
}

__device__ __forceinline__ void final_block(const CUtensorMap* tm, uint32_t sb, int cl, int rank, int un, int b, int barid) {
    uint32_t oaddr, obar;
    asm("mapa.shared::cluster.u32 %0,%1,%2;\n" : "=r"(oaddr) : "r"(sb + OFF_OUT + b * 2048 + un * 16), "r"(rank ^ 1));
    asm("mapa.shared::cluster.u32 %0,%1,%2;\n" : "=r"(obar) : "r"(sb + OFF_MB_OUT + 8 * b), "r"(rank ^ 1));
    const uint32_t orow = sb + OFF_ROWS + b * 4096 + (un >> 6) * 2048 + (un & 63) * 16;
    const uint32_t sw = ((2 * un) ^ ((un >> 1) & 0x18)) * 4 + b * 1024;
    const uint32_t psel = rank ? 0x7632u : 0x5410u;
    uint2 ya[4], yb[4];
    const uint4 gw = lds128(sb + OFF_GT + (b * 256 + 2 * un) * 8);
#pragma unroll
    for (int c = 0; c < 4; ++c) {
        ya[c] = lds64(sb + OFF_S1P + c * 8192 + sw);
        yb[c] = lds64(sb + OFF_S1P + c * 8192 + 4096 + sw);
    }
    if (b > 0) {
        mbar_wait(sb + OFF_MB_P + 8 * b);
#pragma unroll
        for (int c = 0; c < 4; ++c) {
            const uint2 za = lds64(sb + OFF_PG2 - 1024 + c * 6144 + sw);
            const uint2 zb = lds64(sb + OFF_PG2 - 1024 + c * 6144 + 3072 + sw);
            ya[c].x = badd2(ya[c].x, za.x); ya[c].y = badd2(ya[c].y, za.y);
            yb[c].x = badd2(yb[c].x, zb.x); yb[c].y = badd2(yb[c].y, zb.y);
        }
    }
    uint32_t o0[4], o1[4];
#pragma unroll
    for (int c = 0; c < 4; ++c) {
        o0[c] = bfma2(ya[c].x, gw.x, bmul2(yb[c].x, gw.y));
        o1[c] = bfma2(ya[c].y, gw.z, bmul2(yb[c].y, gw.w));
    }
    asm volatile("st.async.weak.shared::cluster.mbarrier::complete_tx::bytes.v4.b32 [%0],{%1,%2,%3,%4},[%5];\n"
                 :: "r"(oaddr), "r"(__byte_perm(o0[0], o0[1], psel ^ 0x2222u)), "r"(__byte_perm(o0[2], o0[3], psel ^ 0x2222u)),
                    "r"(__byte_perm(o1[0], o1[1], psel ^ 0x2222u)), "r"(__byte_perm(o1[2], o1[3], psel ^ 0x2222u)),
                    "r"(obar) : "memory");
    sts64(orow + rank * 8, __byte_perm(o0[0], o0[1], psel), __byte_perm(o0[2], o0[3], psel));
    sts64(orow + 1024 + rank * 8, __byte_perm(o1[0], o1[1], psel), __byte_perm(o1[2], o1[3], psel));
    mbar_wait_cluster(sb + OFF_MB_OUT + 8 * b);
    const uint4 pe = lds128(sb + OFF_OUT + b * 2048 + un * 16);
    sts64(orow + 8 - rank * 8, pe.x, pe.y);
    sts64(orow + 1032 - rank * 8, pe.z, pe.w);
    asm volatile("fence.proxy.async.shared::cta;\n" ::: "memory");
    asm volatile("bar.sync %0, 128;\n" :: "r"(barid) : "memory");
    if (un == 0) {
        asm volatile("cp.async.bulk.tensor.4d.global.shared::cta.bulk_group [%0,{%1,%2,%3,%4}],[%5];\n"
                     :: "l"(tm), "r"(8 * cl), "r"(64 * rank), "r"(0), "r"(2 * b), "r"(sb + OFF_ROWS + b * 4096) : "memory");
        asm volatile("cp.async.bulk.commit_group;\n" ::: "memory");
    }
}

__global__ void __cluster_dims__(2, 1, 1) __launch_bounds__(NTHREADS, 1)
fused_s4d_kernel(const __grid_constant__ Params prm, const __grid_constant__ CUtensorMap tm_in,
                 const __grid_constant__ CUtensorMap tm_out) {
    extern __shared__ __align__(1024) unsigned char smem[];
    const uint32_t sb = (uint32_t)__cvta_generic_to_shared(smem);
    const int tid = threadIdx.x, warp = tid >> 5, lane = tid & 31;
    const int rank = blockIdx.x & 1, cl = blockIdx.x >> 1;
    if (warp != 8) asm volatile("barrier.cluster.arrive.relaxed.aligned;\n" ::: "memory");
    STAMP(0);
    if (tid == 128) GSTAMP(0);

    if (warp >= 8) {
        const int un = tid - 256;
        if (warp == 8) {
            if (lane == 0) {
                asm volatile("prefetch.tensormap [%0];\n" :: "l"(&tm_in) : "memory");
                asm volatile("prefetch.tensormap [%0];\n" :: "l"(&tm_out) : "memory");
                mbar_init(sb + OFF_MB_U, 1);
                mbar_init(sb + OFF_MB_P, 16);
#pragma unroll
                for (int i = 1; i < 4; ++i) mbar_init(sb + OFF_MB_P + 8 * i, 4);
#pragma unroll
                for (int i = 0; i < 4; ++i) mbar_init(sb + OFF_MB_OUT + 8 * i, 1);
                mbar_expect(sb + OFF_MB_U, 32768);
#pragma unroll
                for (int i = 0; i < 4; ++i) mbar_expect(sb + OFF_MB_OUT + 8 * i, 2048);
                asm volatile("fence.mbarrier_init.release.cluster;\n" ::: "memory");
                asm volatile("fence.proxy.async.shared::cta;\n" ::: "memory");
            }
            __syncwarp();
            asm volatile("barrier.cluster.arrive.relaxed.aligned;\n" ::: "memory");
        }
        asm volatile("barrier.cluster.wait.acquire.aligned;\n" ::: "memory");
        if (un == 0) {
            asm volatile("cp.async.bulk.tensor.3d.shared::cluster.global.mbarrier::complete_tx::bytes.multicast::cluster "
                         "[%0],[%1,{%2,%3,%4}],[%5],%6;\n"
                         :: "r"(sb + OFF_U + rank * 16384), "l"(&tm_in), "r"(8 * cl), "r"(0), "r"(8 * rank), "r"(sb + OFF_MB_U),
                            "h"((uint16_t)3) : "memory");
        }
        STAMP(9);
        {
            const uint32_t a2 = sb + OFF_SG2 + (warp - 8) * SG2_CH;
            sts128(a2 + (lane < 16 ? G2_W5 : G2_W3) + ((lane & 15) + ((lane >> 3) & 1)) * 16, 0, 0, 0, 0);
            if (lane < 16) sts128(a2 + (lane < 4 ? G2_W9E : lane < 8 ? G2_W9O : lane < 12 ? G2_W7E : G2_W7O) + (lane & 3) * 16, 0, 0, 0, 0);
            sts128(sb + OFF_V + (warp - 8) * V_CH + (lane >> 4) * V_H + (lane & 15) * 16, 0, 0, 0, 0);
            if (un == 0) sts128(sb + OFF_ZERO, 0, 0, 0, 0);
        }
        const int g = lane >> 2, q = lane & 3;
        uint32_t epoch = 0;
        if (warp == 8) asm volatile("ld.relaxed.gpu.global.u32 %0,[%1];\n" : "=r"(epoch) : "l"(&g_epoch) : "memory");
        uint4 gx[8], gwv[4];
        const uint4* ur = reinterpret_cast<const uint4*>(prm.u) + (size_t)(blockIdx.x * 16 + g) * 64 + (warp - 8) * 16 + q;
        const uint4* wr = reinterpret_cast<const uint4*>(prm.gw) + (warp - 8) * 16 + q;
#pragma unroll
        for (int j = 0; j < 4; ++j) { gx[2 * j] = __ldg(ur + 4 * j); gx[2 * j + 1] = __ldg(ur + 8 * 64 + 4 * j); gwv[j] = __ldg(wr + 4 * j); }
        {
            float gs[4] = {0.f, 0.f, 0.f, 0.f}, gt[4] = {0.f, 0.f, 0.f, 0.f};
#pragma unroll
            for (int j = 0; j < 4; ++j) {
                uint32_t a[4], b[4];
                a[0] = bmul2(gx[2 * j].x, gwv[j].x); a[1] = bmul2(gx[2 * j + 1].x, gwv[j].x);
                a[2] = bmul2(gx[2 * j].y, gwv[j].y); a[3] = bmul2(gx[2 * j + 1].y, gwv[j].y);
                b[0] = bmul2(gx[2 * j].z, gwv[j].z); b[1] = bmul2(gx[2 * j + 1].z, gwv[j].z);
                b[2] = bmul2(gx[2 * j].w, gwv[j].w); b[3] = bmul2(gx[2 * j + 1].w, gwv[j].w);
                mma_bf16(gs, a, 0x3F803F80u, 0x3F803F80u);
                mma_bf16(gt, b, 0x3F803F80u, 0x3F803F80u);
            }
            if (q == 0) {
                sts32(sb + OFF_GPART + ((warp - 8) * 16 + g) * 4, __float_as_uint(gs[0] + gt[0]));
                sts32(sb + OFF_GPART + ((warp - 8) * 16 + g + 8) * 4, __float_as_uint(gs[2] + gt[2]));
            }
            asm volatile("bar.sync 1, 128;\n" ::: "memory");
            if (warp == 8) {
                const uint32_t tg = (epoch + 1u) & 3u;
                if (lane < 16) {
                    float t = 0.f;
#pragma unroll
                    for (int w = 0; w < 4; ++w) t += __uint_as_float(lds32(sb + OFF_GPART + (w * 16 + lane) * 4));
                    const uint32_t wd = gate_word(t) | ((tg & 1u) << 15) | ((tg & 2u) << 30);
                    asm volatile("st.relaxed.gpu.global.u32 [%0],%1;\n" :: "l"(&g_gate[blockIdx.x * 16 + lane]), "r"(wd) : "memory");
                }
                if (lane == 0) {
                    sts32(sb + OFF_TAG, ((tg & 1u) << 15) | ((tg & 2u) << 30));
                    sts32(sb + OFF_TAG + 4, epoch + 1u);
                }
            }
        }
        STAMP(10);
        mbar_wait(sb + OFF_MB_U);
        STAMP(2);
        const int pi = lane >> 4;
#pragma unroll
        for (int it = 0; it < 2; ++it) {
            const int rho = ((warp - 8) + 4 * it) * 16 + (lane & 15);
            const uint32_t ua = sb + OFF_U + rho * 16 + rank * 8 + pi * 4;
            uint32_t v[16];
#pragma unroll
            for (int j = 0; j < 16; ++j) v[j] = lds32(ua + j * 2048);
            const uint32_t a = sb + OFF_V + (2 * pi) * V_CH + (16 + rho) * 16;
            store_pair(a, a + V_CH, v[0], v[1], v[2], v[3], v[4], v[5], v[6], v[7]);
            store_pair(a + V_H, a + V_H + V_CH, v[8], v[9], v[10], v[11], v[12], v[13], v[14], v[15]);
        }
        asm volatile("fence.proxy.async.shared::cta;\n" ::: "memory");
        asm volatile("bar.arrive 2, 384;\n" ::: "memory");
        STAMP(3);
        asm volatile("bar.sync 1, 128;\n" ::: "memory");
#pragma unroll 1
        for (int it = 0; it < 3; ++it) {
            if (it == 2) {
                asm volatile("bar.arrive 3, 256;\n" ::: "memory");
                STAMP(4);
            }
            if (it == A_SPLIT) asm volatile("bar.sync 8, 384;\n" ::: "memory");
            const int rho = it * 32 + lane;
            const uint32_t va = sb + OFF_V + (warp - 8) * V_CH + (16 + rho) * 16;
            const uint4 e0 = lds128(va + V_H - 16), e1 = lds128(va), e2 = lds128(va + V_H), e3 = lds128(va + 16);
            const uint32_t E[13] = {e0.z, e0.w, e1.x, e1.y, e1.z, e1.w, e2.x, e2.y, e2.z, e2.w, e3.x, e3.y, e3.z};
            uint32_t O[12], P2[12], W3[12], P4[11], W5[11];
#pragma unroll
            for (int k = 0; k < 12; ++k) { O[k] = __byte_perm(E[k], E[k + 1], 0x5432); P2[k] = badd2(E[k], O[k]); }
#pragma unroll
            for (int k = 1; k < 12; ++k) W3[k] = badd2(O[k - 1], P2[k]);
#pragma unroll
            for (int k = 0; k < 11; ++k) P4[k] = badd2(P2[k], P2[k + 1]);
#pragma unroll
            for (int k = 2; k < 11; ++k) W5[k] = badd2(P4[k - 1], E[k + 1]);
            const uint32_t s2a = sb + OFF_SG2 + (warp - 8) * SG2_CH;
            const int c5 = 2 * rho + 16;
            const uint32_t a5 = s2a + G2_W5 + (c5 + (c5 >> 3)) * 16, a3 = a5 + (G2_W3 - G2_W5);
            sts128(a5, W5[2], W5[3], W5[4], W5[5]); sts128(a5 + 16, W5[6], W5[7], W5[8], W5[9]);
            sts128(a3, W3[4], W3[5], W3[6], W3[7]); sts128(a3 + 16, W3[8], W3[9], W3[10], W3[11]);
            if (it < 2) {
                uint32_t W7[8], W9[8];
#pragma unroll
                for (int k = 0; k < 8; ++k) { W7[k] = badd2(W3[k + 1], P4[k + 2]); W9[k] = badd2(P4[k], W5[k + 3]); }
                const uint32_t a9 = s2a + (rho + 4) * 16, ap = s2a + rho * 16;
                sts128(a9 + G2_W9E, W9[0], W9[1], W9[2], W9[3]); sts128(a9 + G2_W9O, W9[4], W9[5], W9[6], W9[7]);
                sts128(a9 + G2_W7E, W7[0], W7[1], W7[2], W7[3]); sts128(a9 + G2_W7O, W7[4], W7[5], W7[6], W7[7]);
                sts128(ap + G2_P2E, P2[0], P2[1], P2[2], P2[3]); sts128(ap + G2_P2O, P2[4], P2[5], P2[6], P2[7]);
                if (rho == 0) {
                    const uint32_t n12 = plo(E[2], P2[2]);
                    sts128(a5 - 32, 0, 0, 0, n12);
                    sts128(a3 - 32, 0, W3[1], W3[2], W3[3]);
                    sts128(a9 + G2_W9O - 16, 0, 0, n12, __byte_perm(W3[2], P4[2], 0x5432));
                    sts128(a9 + G2_W7O - 16, 0, 0, E[2] << 16, __byte_perm(P2[2], W3[2], 0x7610));
                }
            }
        }
        asm volatile("bar.arrive 4, 256;\n" ::: "memory");
        if (A_SPLIT == 3) asm volatile("bar.sync 8, 384;\n" ::: "memory");
        {
            const int uc = un;
            const uint32_t tagw = lds32(sb + OFF_TAG);
            bool done = false;
            const int tb0 = (uc >> 5) * 256 + (uc & 31) * 4;
#pragma unroll 1
            for (int tries = 0; tries < 8192 && !done; ++tries) {
                uint4 v[4];
#pragma unroll
                for (int i = 0; i < 4; ++i)
                    asm volatile("ld.relaxed.gpu.global.v4.u32 {%0,%1,%2,%3},[%4];\n"
                                 : "=r"(v[i].x), "=r"(v[i].y), "=r"(v[i].z), "=r"(v[i].w)
                                 : "l"(&g_gate[tb0 + (i >> 1) * 1024 + (i & 1) * 128]) : "memory");
                uint32_t bad = 0;
#pragma unroll
                for (int i = 0; i < 4; ++i)
                    bad |= (v[i].x ^ tagw) | (v[i].y ^ tagw) | (v[i].z ^ tagw) | (v[i].w ^ tagw);
                done = __all_sync(0xffffffffu, (bad & 0x80008000u) == 0);
                if (done) {
#pragma unroll
                    for (int i = 0; i < 2; ++i) {
                        const uint4 a = v[2 * i], b = v[2 * i + 1];
                        const uint32_t d = sb + OFF_GT + (i * 512 + uc * 4) * 8;
                        sts128(d, plo(a.x, b.x) & 0x7FFF7FFFu, phi(a.x, b.x) & 0x7FFF7FFFu, plo(a.y, b.y) & 0x7FFF7FFFu, phi(a.y, b.y) & 0x7FFF7FFFu);
                        sts128(d + 16, plo(a.z, b.z) & 0x7FFF7FFFu, phi(a.z, b.z) & 0x7FFF7FFFu, plo(a.w, b.w) & 0x7FFF7FFFu, phi(a.w, b.w) & 0x7FFF7FFFu);
                    }
                } else {
                    __nanosleep(64);
                }
            }
            if (!done) {
#pragma unroll 1
                for (int k = 0; k < 512; ++k) {
                    const int t = (k >> 8) * 1024 + (uc >> 5) * 256 + (k & 255);
                    float s = 0.f;
#pragma unroll 1
                    for (int j = 0; j < 8; ++j) {
                        const uint32_t pr = bmul2(reinterpret_cast<const uint32_t*>(prm.u)[t * 256 + j * 32 + lane],
                                                  reinterpret_cast<const uint32_t*>(prm.gw)[j * 32 + lane]);
                        s += bf_lo(pr) + bf_hi(pr);
                    }
#pragma unroll
                    for (int o = 16; o > 0; o >>= 1) s += __shfl_xor_sync(0xffffffffu, s, o);
                    if (lane == 0) {
                        const uint32_t wd = gate_word(s);
                        const uint32_t d = sb + OFF_GT + ((t >> 8) * 128 + (t & 127)) * 8 + ((t >> 7) & 1) * 2;
                        asm volatile("st.shared.u16 [%0],%1;\n" :: "r"(d), "h"((uint16_t)(wd & 0xFFFFu)) : "memory");
                        asm volatile("st.shared.u16 [%0],%1;\n" :: "r"(d + 4), "h"((uint16_t)(wd >> 16)) : "memory");
                    }
                }
            }
        }
        asm volatile("bar.sync 1, 128;\n" ::: "memory");
        STAMP(11);
        if (un == 32) {
            asm volatile("{.reg .pred p; .reg .u32 n;\n"
                         "atom.relaxed.gpu.global.inc.u32 n,[%0],%2;\n"
                         "setp.eq.u32 p,n,%2;\n"
                         "@p st.relaxed.gpu.global.u32 [%1],%3;}\n"
                         :: "l"(&g_arrived), "l"(&g_epoch), "r"(gridDim.x - 1), "r"(lds32(sb + OFF_TAG + 4)) : "memory");
        }
        __syncwarp();
        asm volatile("bar.arrive 10, 256;\n" ::: "memory");
        mbar_wait(sb + OFF_MB_P);
#pragma unroll 1
        for (int b = 0; b < 4; b += (b == 1) ? 2 : 1) {
            final_block(&tm_out, sb, cl, rank, un, b, 1);
            STAMP(5 + b);
        }
        if (un == 0) {
            asm volatile("cp.async.bulk.wait_group.read 0;\n" ::: "memory");
            STAMP(13);
            GSTAMP(1);
        }
        return;
    }

    const int ch = warp & 3, role = warp >> 2;
    const int chg = 8 * cl + 4 * rank + ch;
    const int g = lane >> 2, q = lane & 3;

    uint2 pLA, pAI, pCR, pCI;
    {
        const size_t o = (size_t)chg * 128 + lane * 4;
        pLA = __ldg(reinterpret_cast<const uint2*>(prm.p[role][0] + o));
        pAI = __ldg(reinterpret_cast<const uint2*>(prm.p[role][1] + o));
        pCR = __ldg(reinterpret_cast<const uint2*>(prm.p[role][2] + o));
        pCI = __ldg(reinterpret_cast<const uint2*>(prm.p[role][3] + o));
    }
    const float log_dt = __bfloat162float(prm.p[role][4][chg]);
    const float dskip = __bfloat162float(prm.p[role][5][chg]);

    const uint32_t kt = sb + OFF_KT + warp * KT_W;
    {
        if (lane < 30) sts64(kt + KT_WD1 + (lane < 14 ? lane : 258 + lane) * 8, 0u, 0u);
        const uint32_t z2 = kt + KT_WD4 + (lane < 7 ? lane : 64 + lane) * 4;
        if (lane < 16) { sts32(z2, 0u); sts32(z2 + 320, 0u); }
    }
    float dt = 0.f, fscale = 0.f, cinv = 0.f, f0 = 0.f;
    float dk[5][4];
#pragma unroll
    for (int j = 0; j < 5; ++j) { dk[j][0] = dk[j][1] = dk[j][2] = dk[j][3] = 0.f; }
    {
        const uint32_t tb = sb + OFF_FT + warp * FT_W;
        const int mat = lane >> 3, rr = lane & 7;
        const uint32_t stb = tb + (71 * rr + 8 * (mat & 1)) * 16, stc = tb + (71 * rr + 64 + (mat & 1)) * 16;
        const uint32_t ld0 = tb + ((mat & 1) ? 64 + (mat >> 1) : 8 * (mat >> 1) + rr) * 16;
        const uint32_t ld1 = tb + (16 + 8 * mat + rr) * 16;
        const uint32_t ld2 = tb + ((mat & 2) ? 64 + mat : 48 + 8 * mat + rr) * 16;
        const uint32_t ld3 = tb + (71 * (mat >> 1) + 68 + (mat & 1)) * 16;
#pragma unroll
        for (int r = 0; r < 2; ++r) {
            uint32_t wLA = 0u, wAI = 0u, wCR = 0u, wCI = 0u;
            if (r == 0) {
                dt = bf_round(expf(log_dt));
                uint32_t m = max(max(max(pCR.x & 0x7F80u, (pCR.x >> 16) & 0x7F80u), max(pCR.y & 0x7F80u, (pCR.y >> 16) & 0x7F80u)),
                                 max(max(pCI.x & 0x7F80u, (pCI.x >> 16) & 0x7F80u), max(pCI.y & 0x7F80u, (pCI.y >> 16) & 0x7F80u)));
                m = __reduce_max_sync(0xffffffffu, m) >> 7;
                m = min(max(m, 1u), 253u);
                cinv = __uint_as_float((254u - m) << 23);
                fscale = 2.0f * dt * __uint_as_float(m << 23);
                wLA = pLA.x; wAI = pAI.x; wCR = pCR.x; wCI = pCI.x;
                STAMP(1);
            } else if (r == 1) {
                f0 = (bf_lo(pCR.x) + bf_hi(pCR.x)) + (bf_lo(pCR.y) + bf_hi(pCR.y));
#pragma unroll
                for (int o = 16; o > 0; o >>= 1) f0 += __shfl_xor_sync(0xffffffffu, f0, o);
                f0 = fmaf(2.0f * dt, f0, dskip);
                wLA = pLA.y; wAI = pAI.y; wCR = pCR.y; wCI = pCI.y;
            }
            float ea, eb;
            asm("ex2.approx.ftz.f32 %0,%1;\n" : "=f"(ea) : "f"(bf_lo(wLA) * 1.4426950408889634f));
            asm("ex2.approx.ftz.f32 %0,%1;\n" : "=f"(eb) : "f"(bf_hi(wLA) * 1.4426950408889634f));
            const uint32_t e2 = pack_bf16(ea, eb);
            const float ala = (-bf_lo(e2) * dt) * 1.4426950408889634f, alb = (-bf_hi(e2) * dt) * 1.4426950408889634f;
            const float aia = bf_lo(wAI) * dt, aib = bf_hi(wAI) * dt;
            const pc C = mk64(pack_f16(bf_lo(wCR) * cinv, bf_hi(wCR) * cinv), pack_f16(bf_lo(wCI) * cinv, bf_hi(wCI) * cinv));
            {
                c32 a = cexp_seed(ala, -aia, 16.f), b = cexp_seed(alb, -aib, 16.f);
                const pc f1 = mkp(a, b); a = csq(a); b = csq(b);
                const pc f2 = mkp(a, b); a = csq(a); b = csq(b);
                const pc f4 = mkp(a, b); a = csq(a); b = csq(b);
                stp(stb, 0x3C003C00ull);
                stp(stb + 16, f1); stp(stb + 32, f2); stp(stb + 64, f4); stp(stc, mkp(a, b));
                const pc f3 = pmul(f1, f2);
                stp(stb + 48, f3); stp(stb + 80, pmul(f1, f4)); stp(stb + 96, pmul(f2, f4)); stp(stb + 112, pmul(f3, f4));
                a = cexp_seed(ala, aia, 1.f); b = cexp_seed(alb, aib, 1.f);
                const pc w1 = mkp(a, b); a = csq(a); b = csq(b);
                const pc w2 = mkp(a, b); a = csq(a); b = csq(b);
                const pc w4 = mkp(a, b); a = csq(a); b = csq(b);
                const pc w8 = mkp(a, b);
                stp(stc + 32, w1);
                pc D[4];
                D[0] = pmul(C, w1); D[1] = pmul(D[0], w2); D[2] = pmul(D[0], w4); D[3] = pmul(D[1], w4);
#pragma unroll
                for (int j = 0; j < 4; ++j) { stp(stb + 256 + 16 * j, D[j]); stp(stb + 320 + 16 * j, pmul(D[j], w8)); }
                a = cexp_seed(ala, aia, 256.f); b = cexp_seed(alb, aib, 256.f);
                const pc w256 = mkp(a, b); a = csq(a); b = csq(b);
                const pc w512 = mkp(a, b); a = csq(a); b = csq(b);
                const pc w1024 = mkp(a, b);
                stp(stc + 64, w256);
                D[0] = pmul(C, w4); D[1] = pmul(C, w8); D[2] = pmul(D[0], w8); D[3] = pmul(D[1], w8);
#pragma unroll
                for (int j = 0; j < 4; ++j) {
                    const pc t = pmul(D[j], w512);
                    stp(stb + 512 + 16 * j, t); stp(stb + 576 + 16 * j, pmul(t, w256));
                }
#pragma unroll
                for (int j = 0; j < 2; ++j) {
                    const pc t = pmul(D[2 * j + 1], w1024), t2 = pmul(t, w256);
                    stp(stb + 768 + 16 * j, t); stp(stb + 800 + 16 * j, t2);
                    stp(stb + 832 + 16 * j, pmul(t, w512)); stp(stb + 864 + 16 * j, pmul(t2, w512));
                }
            }
            __syncwarp();
#pragma unroll
            for (int s = 0; s < 8; s += 2) {
                uint32_t W[4];
                ldsm4(W, ld3 + s * 1136);
#pragma unroll
                for (int h = 0; h < 2; ++h) {
                    uint32_t L0[4], L1[4], L2[4];
                    ldsm4(L0, ld0 + (s + h) * 1136); ldsm4(L1, ld1 + (s + h) * 1136); ldsm4(L2, ld2 + (s + h) * 1136);
                    uint32_t A[4];
                    A[0] = L0[0]; A[2] = L0[2];
                    asm("{.reg .b32 t0,t1,n; mul.rn.f16x2 t0,%2,%4; mul.rn.f16x2 t1,%3,%4; neg.f16x2 n,%3;\n"
                        "fma.rn.f16x2 %0,n,%5,t0; fma.rn.f16x2 %1,%2,%5,t1;}\n"
                        : "=r"(A[1]), "=r"(A[3]) : "r"(L0[0]), "r"(L0[2]), "r"(L0[1]), "r"(L0[3]));
                    const pc t1 = pmul(mk64(L1[0], L1[1]), mk64(L2[2], L2[3]));
                    const pc t2 = pmul(t1, mk64(W[2 * h], W[2 * h + 1]));
                    mma_f16(dk[0], A, L1[0], L1[1]);
                    mma_f16(dk[3], A, L1[2], L1[3]);
                    mma_f16(dk[4], A, L2[0], L2[1]);
                    mma_f16p(dk[1], A, t1);
                    mma_f16p(dk[2], A, t2);
                }
            }
            __syncwarp();
        }
    }
    asm volatile("bar.arrive 8, 384;\n" ::: "memory");
    STAMP(2);

    {
        const bool last = (lane == 31);
#pragma unroll
        for (int j = 0; j < 5; ++j)
#pragma unroll
            for (int c = 0; c < 4; ++c) dk[j][c] *= fscale;
        const float f256 = dk[1][3], f512 = dk[2][3], f1024 = dk[3][3];
        if (last) { dk[2][2] -= f512; dk[2][3] = 0.f; }
        const float n0 = __shfl_sync(0xffffffffu, dk[0][0], (lane + 1) & 31), n1 = __shfl_sync(0xffffffffu, dk[0][2], (lane + 1) & 31);
        const float p0 = __shfl_sync(0xffffffffu, lane == 31 ? f256 : dk[2][1], (lane + 31) & 31);
        const float p1 = __shfl_sync(0xffffffffu, lane == 31 ? dk[2][1] : dk[2][3], (lane + 31) & 31);
#pragma unroll
        for (int hh = 0; hh < 2; ++hh) {
            const float a = dk[0][2 * hh], b = dk[1][2 * hh], c = dk[0][2 * hh + 1], d = dk[1][2 * hh + 1];
            const float an = hh == 0 ? (last ? n1 : n0) : (last ? d : n1);
            const uint32_t wa = kt + KT_WD1 + (16 + 4 * lane + 128 * hh) * 8;
            const float be = dk[2][2 * hh], al = dk[2][2 * hh + 1];
            const uint32_t aa = pack_bf16(al, al);
            const uint32_t w0 = pack_bf16(b, a), w1 = pack_bf16(c, b), w2 = pack_bf16(d, c), w3 = pack_bf16(an, d);
            sts128(wa, w0, pack_bf16(be, hh == 0 ? p0 : p1), w1, pack_bf16(al, be));
            sts128(wa + 16, w2, aa, w3, aa);
            if (hh == 1 && lane >= 28) {
                sts32(wa - 2048 + 4, w0); sts32(wa - 2048 + 12, w1); sts32(wa - 2048 + 20, w2); sts32(wa - 2048 + 28, w3);
            }
        }
        if (lane == 0) { sts32(kt + KT_WD1 + 14 * 8, pack_bf16(f0, 0.f)); sts32(kt + KT_WD1 + 15 * 8, pack_bf16(dk[0][0], f0)); }
#pragma unroll
        for (int hh = 0; hh < 2; ++hh) {
            const int i = g + 8 * hh;
            sts32(kt + KT_WD4 + (2 * i + (q & 1) + 32 * (q >> 1) + 8) * 4, pack_bf16(dk[3][2 * hh + 1], dk[3][2 * hh]));
            sts32(kt + KT_WD4 + 320 + (i + 16 * q + 7) * 4, pack_bf16(dk[4][2 * hh + 1], dk[4][2 * hh]));
        }
        if (last) {
            sts32(kt + KT_WD4 + 7 * 4, pack_bf16(f512, 0.f));
            sts32(kt + KT_FIX, pack_bf16(f1024, f1024));
        }
    }
    STAMP(3);
    asm volatile("bar.sync 2, 384;\n" ::: "memory");
    STAMP(6);

    const uint32_t ktA = sb + OFF_KT + ch * KT_W, ktB = ktA + 4 * KT_W;
    const int mat = lane >> 3, rr = lane & 7;
    const int np = 4 * (g & 1) + (g >> 1);
    uint32_t k4[9][2][2], k8[8][2][2], kf[2];
    const uint32_t o4 = KT_WD4 + (g - q + 7) * 4;
    const uint32_t o8 = KT_WD4 + 320 + (np + 7 - q) * 4;
#define K_LOAD(DST, OFF, KS)                                                                                 \
        { DST[KS][0][0] = lds32(ktA + OFF + (8 * (KS)) * 4); DST[KS][0][1] = lds32(ktA + OFF + (8 * (KS) - 4) * 4); \
          DST[KS][1][0] = lds32(ktB + OFF + (8 * (KS)) * 4); DST[KS][1][1] = lds32(ktB + OFF + (8 * (KS) - 4) * 4); }
    {
        const int rb = ch >> 1, br = ch & 1;
        const int urole = __shfl_sync(0xffffffffu, role, 0);
        uint32_t wa = sb + OFF_KT + (br * 4 + role) * KT_W + KT_WD1 + (14 + 8 * rb + g - 2 * q) * 8;
        uint2 af[17][2];
#define A_LOAD(S) { af[S][0] = lds64(wa + 128 * (S)); af[S][1] = lds64(wa + 128 * (S) - 64); }
        if (urole) asm volatile("bar.sync 9, 256;\n" ::: "memory");
#pragma unroll
        for (int s = 0; s < 9; ++s) A_LOAD(s);
#pragma unroll
        for (int cc = 0; cc < 2; ++cc) {
#pragma unroll
            for (int s = 9; s < 17; ++s) A_LOAD(s);
            const int c = urole + 2 * cc;
            const uint32_t desc = (((sb + OFF_V + c * V_CH + 256) & 0x3FFFFu) >> 4) | ((V_H >> 4) << 16);
            float d[64];
            if (urole | cc) asm volatile("bar.sync %0, 256;\n" :: "r"(5 + urole) : "memory");
            else asm volatile("bar.arrive 9, 256;\n" ::: "memory");
            asm volatile("wgmma.fence.sync.aligned;\n" ::: "memory");
#pragma unroll
            for (int s = 0; s < 9; ++s) wgmma_n128(d, af[s][0].x, af[s][0].y, af[s][1].x, af[s][1].y, desc - s, s);
            asm volatile("wgmma.commit_group.sync.aligned;\n" ::: "memory");
#pragma unroll
            for (int s = 9; s < 17; ++s)
                wgmma_n128(d, s < 16 ? af[s][0].x : 0u, af[s][0].y, s < 16 ? af[s][1].x : 0u, af[s][1].y, desc - s, 1);
            asm volatile("wgmma.commit_group.sync.aligned;\n" ::: "memory");
            if (!(urole & cc)) asm volatile("bar.arrive %0, 256;\n" :: "r"(6 - urole) : "memory");
            asm volatile("wgmma.wait_group.sync.aligned 1;\n" ::: "memory");
            wa += 2 * KT_W;
            if (cc == 0) {
#pragma unroll
                for (int s = 0; s < 9; ++s) A_LOAD(s);
            } else {
#pragma unroll
                for (int ks = 0; ks < 9; ++ks) K_LOAD(k4, o4, ks);
            }
            asm volatile("wgmma.wait_group.sync.aligned 0;\n" ::: "memory");
#pragma unroll
            for (int i = 0; i < 64; ++i) asm volatile("" : "+f"(d[i]) :: "memory");
            if (urole & cc) asm volatile("bar.arrive 7, 256;\n" ::: "memory");
            if (cc == 0) STAMP(4); else STAMP(5);
            const uint32_t dst = sb + OFF_S1P + c * 8192 + br * 4096 + (32 * q + g) * 4;
#pragma unroll
            for (int j = 0; j < 16; j += 2)
#pragma unroll
                for (int e = 0; e < 2; ++e) {
                    const float y0 = j >= 2 ? d[4 * j + e] + d[4 * j - 6 + e] : d[4 * j + e];
                    const float y1 = j >= 2 ? d[4 * j + 4 + e] + d[4 * j - 2 + e] : d[4 * j + 4 + e];
                    sts32(dst + j * 256 + ((16 * e + 8 * rb) ^ (8 * q)) * 4, pack_bf16(y0, y1));
                }
            __syncwarp();
            if (lane == 0) mbar_arrive(sb + OFF_MB_P);
        }
#undef A_LOAD
    }
    STAMP(7);

    {
        const uint32_t s2 = sb + OFF_SG2 + ch * SG2_CH;
        const uint32_t b4 = s2 + ((rr & 1) ? G2_W3 : G2_W5) + (18 + 9 * (mat & 1) + 4 * (mat >> 1) + (rr >> 1)) * 16;
        const int d8 = 6 + 8 * (mat >> 1) + rr + (mat & 1);
        const uint32_t b8 = s2 + ((rr & 1) ? ((d8 & 1) ? G2_W7O : G2_W7E) : ((d8 & 1) ? G2_W9O : G2_W9E)) + (d8 >> 1) * 16;
        const uint32_t bf = s2 + ((mat & 1) ? G2_P2O : G2_P2E) + rr * 16;
        const uint32_t pg = sb + OFF_PG2 + ch * 6144 + (32 * (q >> 1) + g) * 4;
        const int blk = 2 + role;
        const uint32_t c8 = b8 + (4 * blk - 8) * 128, c4 = b4 + (8 * blk - 8) * 144;
#define G2_STORE(ACC, BLK)                                                                                   \
        _Pragma("unroll") for (int tj = 0; tj < 4; tj += 2)                                                  \
            _Pragma("unroll") for (int br = 0; br < 2; ++br)                                                 \
                _Pragma("unroll") for (int c = 0; c < 4; ++c)                                                \
                    sts32(pg + br * 3072 + ((BLK) - 1) * 1024 + tj * 256 + (c >> 1) * 256 +                  \
                          (16 * ((q & 1) ^ (c >> 1)) + 8 * ((c & 1) ^ (q >> 1))) * 4,                        \
                          pack_bf16(ACC[tj][br][c], ACC[tj + 1][br][c]));                                    \
        __syncwarp();                                                                                         \
        if (lane == 0) mbar_arrive(sb + OFF_MB_P + 8 * (BLK));
        uint32_t fa[4], fb[4], fc[4], fd[4], fx[4][2];
        {
            const uint32_t msk = ((np >> 1) == q) ? ((np & 1) ? 0xFFFF0000u : 0x0000FFFFu) : 0u;
            kf[0] = lds32(ktA + KT_FIX) & msk; kf[1] = lds32(ktB + KT_FIX) & msk;
        }
#pragma unroll
        for (int ks = 0; ks < 4; ++ks) K_LOAD(k8, o8, ks);
        if (role) {
#pragma unroll
            for (int ks = 4; ks < 8; ++ks) K_LOAD(k8, o8, ks);
        }
        asm volatile("bar.sync %0, 256;\n" :: "r"(3 + role) : "memory");
        STAMP(8);
        float a8[4][2][4];
#pragma unroll
        for (int tj = 0; tj < 4; ++tj)
#pragma unroll
            for (int br = 0; br < 2; ++br) { a8[tj][br][0] = a8[tj][br][1] = a8[tj][br][2] = a8[tj][br][3] = 0.f; }
        if (role == 0) {
            ldsm4t(fa, b4 - 2 * 144); ldsm4t(fb, b4 - 144);
            asm volatile("bar.sync 7, 256;\n" ::: "memory");
            float a1[4][2][4];
#pragma unroll
            for (int tj = 0; tj < 4; ++tj)
#pragma unroll
                for (int br = 0; br < 2; ++br) { a1[tj][br][0] = a1[tj][br][1] = a1[tj][br][2] = a1[tj][br][3] = 0.f; }
            toep_block<2, 8, -2, 6, 144>(a1, k4, b4, fa, fb);
            G2_STORE(a1, 1);
            STAMP(9);
        } else {
            ldsm4t(fc, b8); ldsm4t(fd, b8 + 128);
            toep_block<1, 7, -4, -1, 128>(a8, k8, b8 + 4 * 128, fc, fd);
        }
#pragma unroll
        for (int tj = 0; tj < 4; ++tj) ldsm2t(fx[tj][0], fx[tj][1], bf + (4 * blk - 8 + tj) * 128);
        ldsm4t(fc, c8); ldsm4t(fd, c8 + 128);
        ldsm4t(fa, c4 - 8 * 144); ldsm4t(fb, c4 - 7 * 144);
#pragma unroll
        for (int tj = 0; tj < 4; ++tj) { mma_bf16_k8(a8[tj][0], fx[tj][0], fx[tj][1], kf[0]); mma_bf16_k8(a8[tj][1], fx[tj][0], fx[tj][1], kf[1]); }
        toep_block<1, 7, 0, 3, 128>(a8, k8, c8, fc, fd);
        float a4[4][2][4];
#pragma unroll
        for (int tj = 0; tj < 4; ++tj)
#pragma unroll
            for (int br = 0; br < 2; ++br) {
                a4[tj][br][0] = a8[tj][br][0]; a4[tj][br][1] = a8[tj][br][2];
                a4[tj][br][2] = a8[tj][br][1]; a4[tj][br][3] = a8[tj][br][3];
            }
        toep_block<2, 8, -8, 6, 144>(a4, k4, c4, fa, fb);
        G2_STORE(a4, blk);
        STAMP(10);
#undef G2_STORE
#undef K_LOAD
    }
    asm volatile("barrier.cluster.wait.acquire.aligned;\n" ::: "memory");
    if (role == 0) {
        asm volatile("bar.sync 10, 256;\n" ::: "memory");
        mbar_wait(sb + OFF_MB_P);
        final_block(&tm_out, sb, cl, rank, tid, 2, 11);
        STAMP(11);
        if (tid == 0) asm volatile("cp.async.bulk.wait_group.read 0;\n" ::: "memory");
    }
}

typedef CUresult (*EncodeFn)(CUtensorMap*, CUtensorMapDataType, cuuint32_t, void*, const cuuint64_t*, const cuuint64_t*,
                             const cuuint32_t*, const cuuint32_t*, CUtensorMapInterleave, CUtensorMapSwizzle,
                             CUtensorMapL2promotion, CUtensorMapFloatOOBfill);

}

extern "C" void kernel_launch(void* const* d_in, const int* in_sizes, int n_in, void* d_out, int out_size) {
    (void)in_sizes; (void)n_in; (void)out_size;
    static EncodeFn encode = nullptr;
    if (!encode) {
        void* fn = nullptr;
        cudaDriverEntryPointQueryResult qr;
        cudaGetDriverEntryPoint("cuTensorMapEncodeTiled", &fn, cudaEnableDefault, &qr);
        encode = (EncodeFn)fn;
        cudaFuncSetAttribute(fused_s4d_kernel, cudaFuncAttributeMaxDynamicSharedMemorySize, SMEM_BYTES);
    }
    CUtensorMap tin, tout;
    {
        cuuint64_t gd[3] = {DCH, 128, 16};
        cuuint64_t gs[2] = {16 * 1024, 1024};
        cuuint32_t bx[3] = {8, 128, 8};
        cuuint32_t es[3] = {1, 1, 1};
        encode(&tin, CU_TENSOR_MAP_DATA_TYPE_BFLOAT16, 3, d_in[0], gd, gs, bx, es, CU_TENSOR_MAP_INTERLEAVE_NONE,
               CU_TENSOR_MAP_SWIZZLE_NONE, CU_TENSOR_MAP_L2_PROMOTION_NONE, CU_TENSOR_MAP_FLOAT_OOB_FILL_NONE);
    }
    {
        cuuint64_t gd[4] = {DCH, 128, 2, 8};
        cuuint64_t gs[3] = {2048, 1024, 256 * 1024};
        cuuint32_t bx[4] = {8, 64, 2, 2};
        cuuint32_t es[4] = {1, 1, 1, 1};
        encode(&tout, CU_TENSOR_MAP_DATA_TYPE_BFLOAT16, 4, d_out, gd, gs, bx, es, CU_TENSOR_MAP_INTERLEAVE_NONE,
               CU_TENSOR_MAP_SWIZZLE_NONE, CU_TENSOR_MAP_L2_PROMOTION_NONE, CU_TENSOR_MAP_FLOAT_OOB_FILL_NONE);
    }
    Params prm;
    prm.u = (const __nv_bfloat16*)d_in[0];
    for (int j = 0; j < 6; ++j) {
        prm.p[0][j] = (const __nv_bfloat16*)d_in[1 + j];
        prm.p[1][j] = (const __nv_bfloat16*)d_in[8 + j];
    }
    prm.gw = (const __nv_bfloat16*)d_in[14];
    fused_s4d_kernel<<<128, NTHREADS, SMEM_BYTES, cudaStreamPerThread>>>(prm, tin, tout);
}
```

```cpp
#include <cuda_runtime.h>
#include <cuda_bf16.h>
#include <cuda_fp16.h>
#include <cuda.h>
#include <stdint.h>

#define PROFILE_CLK 0

namespace {

constexpr int LSEQ = 2048;
constexpr int DCH = 512;
constexpr int NTHREADS = 384;

constexpr int OFF_U = 0;
constexpr int OFF_ROWS = OFF_U;
constexpr int G2_W5 = 0, G2_W3 = 3776, G2_W9E = 7552, G2_W9O = G2_W9E + 1152, G2_W7E = G2_W9O + 1152 + 48,
              G2_W7O = G2_W7E + 1152 + 16, G2_P2E = G2_W7O + 1088 + 64, G2_P2O = G2_P2E + 1024, SG2_CH = 14336;
static_assert((G2_W7O - G2_W9E) % 128 == 64 && (G2_W7E + 16 - G2_W9O) % 128 == 64 && G2_P2O + 1024 <= SG2_CH, "banks");
constexpr int OFF_SG2 = 32768;
constexpr int V_H = 144 * 16, V_CH = 2 * V_H;
constexpr int OFF_V = OFF_SG2 + 4 * SG2_CH;
constexpr int OFF_S1P = OFF_V + 4 * V_CH;
constexpr int OFF_PG2 = OFF_S1P + 32768;
constexpr int OFF_GT = OFF_PG2 + 24576;
constexpr int FT_W = 8 * 71 * 16;
constexpr int OFF_FT = OFF_S1P;
constexpr int KT_W = 2960;
constexpr int KT_WD1 = 0, KT_WD4 = 288 * 8, KT_FIX = KT_WD4 + 2 * 320;
constexpr int OFF_KT = OFF_FT + 8 * FT_W;
constexpr int OFF_OUT = OFF_KT + 8 * KT_W;
constexpr int OFF_MISC = OFF_OUT + 8192;
constexpr int OFF_MB_U = OFF_MISC, OFF_MB_P = OFF_MISC + 8, OFF_MB_OUT = OFF_MISC + 40;
constexpr int OFF_TAG = OFF_MISC + 72;
constexpr int OFF_GPART = OFF_MISC + 128;
constexpr int SMEM_BYTES = OFF_GPART + 256;
static_assert(OFF_V % 128 == 0 && OFF_S1P % 128 == 0 && OFF_KT % 128 == 0 && OFF_OUT % 128 == 0, "align");
static_assert(OFF_GT + 8192 <= OFF_KT && KT_FIX + 4 <= KT_W && SMEM_BYTES <= 232448, "smem");

struct Params {
    const __nv_bfloat16* u;
    const __nv_bfloat16* p[2][6];
    const __nv_bfloat16* gw;
};

__device__ __align__(128) uint32_t g_gate[LSEQ];
__device__ uint32_t g_epoch;
__device__ uint32_t g_arrived;
#define STAMP(i) do {} while (0)
#define GSTAMP(i) do {} while (0)

__device__ __forceinline__ void ldsm4(uint32_t (&r)[4], uint32_t a) {
    asm volatile("ldmatrix.sync.aligned.m8n8.x4.shared.b16 {%0,%1,%2,%3},[%4];\n"
                 : "=r"(r[0]), "=r"(r[1]), "=r"(r[2]), "=r"(r[3]) : "r"(a) : "memory");
}
__device__ __forceinline__ void ldsm4t(uint32_t (&r)[4], uint32_t a) {
    asm volatile("ldmatrix.sync.aligned.m8n8.x4.trans.shared.b16 {%0,%1,%2,%3},[%4];\n"
                 : "=r"(r[0]), "=r"(r[1]), "=r"(r[2]), "=r"(r[3]) : "r"(a) : "memory");
}
__device__ __forceinline__ void ldsm2t(uint32_t& r0, uint32_t& r1, uint32_t a) {
    asm volatile("ldmatrix.sync.aligned.m8n8.x2.trans.shared.b16 {%0,%1},[%2];\n" : "=r"(r0), "=r"(r1) : "r"(a) : "memory");
}
__device__ __forceinline__ void mma_bf16(float (&d)[4], const uint32_t (&a)[4], uint32_t b0, uint32_t b1) {
    asm("mma.sync.aligned.m16n8k16.row.col.f32.bf16.bf16.f32 {%0,%1,%2,%3},{%4,%5,%6,%7},{%8,%9},{%0,%1,%2,%3};\n"
        : "+f"(d[0]), "+f"(d[1]), "+f"(d[2]), "+f"(d[3])
        : "r"(a[0]), "r"(a[1]), "r"(a[2]), "r"(a[3]), "r"(b0), "r"(b1));
}
__device__ __forceinline__ void mma_bf16_k8(float (&d)[4], uint32_t a0, uint32_t a1, uint32_t b0) {
    asm("mma.sync.aligned.m16n8k8.row.col.f32.bf16.bf16.f32 {%0,%1,%2,%3},{%4,%5},{%6},{%0,%1,%2,%3};\n"
        : "+f"(d[0]), "+f"(d[1]), "+f"(d[2]), "+f"(d[3]) : "r"(a0), "r"(a1), "r"(b0));
}
__device__ __forceinline__ void mma_f16(float (&d)[4], const uint32_t (&a)[4], uint32_t b0, uint32_t b1) {
    asm("mma.sync.aligned.m16n8k16.row.col.f32.f16.f16.f32 {%0,%1,%2,%3},{%4,%5,%6,%7},{%8,%9},{%0,%1,%2,%3};\n"
        : "+f"(d[0]), "+f"(d[1]), "+f"(d[2]), "+f"(d[3])
        : "r"(a[0]), "r"(a[1]), "r"(a[2]), "r"(a[3]), "r"(b0), "r"(b1));
}
__device__ __forceinline__ uint32_t lds32(uint32_t a) {
    uint32_t v; asm volatile("ld.shared.u32 %0,[%1];\n" : "=r"(v) : "r"(a) : "memory"); return v;
}
__device__ __forceinline__ uint4 lds128(uint32_t a) {
    uint4 v; asm volatile("ld.shared.v4.u32 {%0,%1,%2,%3},[%4];\n" : "=r"(v.x), "=r"(v.y), "=r"(v.z), "=r"(v.w) : "r"(a) : "memory");
    return v;
}
__device__ __forceinline__ void sts32(uint32_t a, uint32_t v) { asm volatile("st.shared.u32 [%0],%1;\n" :: "r"(a), "r"(v) : "memory"); }
__device__ __forceinline__ void sts128(uint32_t a, uint32_t x, uint32_t y, uint32_t z, uint32_t w) {
    asm volatile("st.shared.v4.u32 [%0],{%1,%2,%3,%4};\n" :: "r"(a), "r"(x), "r"(y), "r"(z), "r"(w) : "memory");
}
__device__ __forceinline__ uint32_t pack_bf16(float lo, float hi) {
    uint32_t r; asm("cvt.rn.bf16x2.f32 %0,%1,%2;\n" : "=r"(r) : "f"(hi), "f"(lo)); return r;
}
__device__ __forceinline__ uint32_t pack_f16(float lo, float hi) {
    uint32_t r; asm("cvt.rn.f16x2.f32 %0,%1,%2;\n" : "=r"(r) : "f"(hi), "f"(lo)); return r;
}
__device__ __forceinline__ uint32_t badd2(uint32_t a, uint32_t b) {
    uint32_t r; asm("add.rn.bf16x2 %0,%1,%2;\n" : "=r"(r) : "r"(a), "r"(b)); return r;
}
__device__ __forceinline__ uint32_t bmul2(uint32_t a, uint32_t b) {
    uint32_t r; asm("mul.rn.bf16x2 %0,%1,%2;\n" : "=r"(r) : "r"(a), "r"(b)); return r;
}
__device__ __forceinline__ void sts64(uint32_t a, uint32_t x, uint32_t y) {
    asm volatile("st.shared.v2.u32 [%0],{%1,%2};\n" :: "r"(a), "r"(x), "r"(y) : "memory");
}
__device__ __forceinline__ uint2 lds64(uint32_t a) {
    uint2 v; asm volatile("ld.shared.v2.u32 {%0,%1},[%2];\n" : "=r"(v.x), "=r"(v.y) : "r"(a) : "memory"); return v;
}
__device__ __forceinline__ uint32_t bfma2(uint32_t a, uint32_t b, uint32_t c) {
    uint32_t r; asm("fma.rn.bf16x2 %0,%1,%2,%3;\n" : "=r"(r) : "r"(a), "r"(b), "r"(c)); return r;
}
__device__ __forceinline__ uint32_t plo(uint32_t a, uint32_t b) { return __byte_perm(a, b, 0x5410); }
__device__ __forceinline__ uint32_t phi(uint32_t a, uint32_t b) { return __byte_perm(a, b, 0x7632); }
__device__ __forceinline__ float bf_lo(uint32_t v) { return __uint_as_float(v << 16); }
__device__ __forceinline__ float bf_hi(uint32_t v) { return __uint_as_float(v & 0xFFFF0000u); }
__device__ __forceinline__ float bf_round(float x) { return __bfloat162float(__float2bfloat16_rn(x)); }

__device__ __forceinline__ void mbar_init(uint32_t a, uint32_t cnt) {
    asm volatile("mbarrier.init.shared.b64 [%0],%1;\n" :: "r"(a), "r"(cnt) : "memory");
}
__device__ __forceinline__ void mbar_arrive(uint32_t a) {
    asm volatile("mbarrier.arrive.shared.b64 _,[%0];\n" :: "r"(a) : "memory");
}
__device__ __forceinline__ void mbar_expect(uint32_t a, uint32_t bytes) {
    asm volatile("mbarrier.arrive.expect_tx.shared.b64 _,[%0],%1;\n" :: "r"(a), "r"(bytes) : "memory");
}
__device__ __forceinline__ void mbar_wait(uint32_t a) {
    uint32_t ok = 0;
#pragma unroll 1
    for (int it = 0; it < (1 << 20) && !ok; ++it)
        asm volatile("{.reg .pred p; mbarrier.try_wait.parity.shared.b64 p,[%1],0; selp.u32 %0,1,0,p;}\n"
                     : "=r"(ok) : "r"(a) : "memory");
}
__device__ __forceinline__ void mbar_wait_cluster(uint32_t a) {
    uint32_t ok = 0;
#pragma unroll 1
    for (int it = 0; it < (1 << 20) && !ok; ++it)
        asm volatile("{.reg .pred p; mbarrier.try_wait.parity.acquire.cluster.shared.b64 p,[%1],0; selp.u32 %0,1,0,p;}\n"
                     : "=r"(ok) : "r"(a) : "memory");
}

struct c32 { float x, y; };
__device__ __forceinline__ c32 csq(c32 z) { c32 r; r.x = fmaf(z.x, z.x, -(z.y * z.y)); r.y = (z.x + z.x) * z.y; return r; }
__device__ __forceinline__ c32 cexp_seed(float al2, float ai, float x) {
    float m, s, c, th = ai * x, e = al2 * x;
    asm("ex2.approx.ftz.f32 %0,%1;\n" : "=f"(m) : "f"(e));
    asm("sin.approx.ftz.f32 %0,%1;\n" : "=f"(s) : "f"(th));
    asm("cos.approx.ftz.f32 %0,%1;\n" : "=f"(c) : "f"(th));
    c32 r; r.x = m * c; r.y = m * s; return r;
}
typedef unsigned long long pc;
__device__ __forceinline__ pc mk64(uint32_t re, uint32_t im) { pc r; asm("mov.b64 %0,{%1,%2};\n" : "=l"(r) : "r"(re), "r"(im)); return r; }
__device__ __forceinline__ pc mkp(c32 a, c32 b) {
    pc r;
    asm("{.reg .b32 x,y; cvt.rn.f16x2.f32 x,%2,%1; cvt.rn.f16x2.f32 y,%4,%3; mov.b64 %0,{x,y};}\n"
        : "=l"(r) : "f"(a.x), "f"(b.x), "f"(a.y), "f"(b.y));
    return r;
}
__device__ __forceinline__ pc pmul(pc z, pc w) {
    pc r;
    asm("{.reg .b32 zr,zi,wr,wi,t0,t1,n; mov.b64 {zr,zi},%1; mov.b64 {wr,wi},%2;\n"
        "mul.rn.f16x2 t0,zr,wr; mul.rn.f16x2 t1,zi,wr; neg.f16x2 n,zi;\n"
        "fma.rn.f16x2 t0,n,wi,t0; fma.rn.f16x2 t1,zr,wi,t1; mov.b64 %0,{t0,t1};}\n"
        : "=l"(r) : "l"(z), "l"(w));
    return r;
}
__device__ __forceinline__ void stp(uint32_t a, pc v) {
    asm volatile("{.reg .b32 x,y; mov.b64 {x,y},%1; stmatrix.sync.aligned.m8n8.x2.shared.b16 [%0],{x,y};}\n"
                 :: "r"(a), "l"(v) : "memory");
}
__device__ __forceinline__ void mma_f16p(float (&d)[4], const uint32_t (&a)[4], pc b) {
    asm("{.reg .b32 x,y; mov.b64 {x,y},%8;\n"
        "mma.sync.aligned.m16n8k16.row.col.f32.f16.f16.f32 {%0,%1,%2,%3},{%4,%5,%6,%7},{x,y},{%0,%1,%2,%3};}\n"
        : "+f"(d[0]), "+f"(d[1]), "+f"(d[2]), "+f"(d[3]) : "r"(a[0]), "r"(a[1]), "r"(a[2]), "r"(a[3]), "l"(b));
}

__device__ __forceinline__ void store_pair(uint32_t a0, uint32_t a1, uint32_t v0, uint32_t v1, uint32_t v2, uint32_t v3,
                                           uint32_t v4, uint32_t v5, uint32_t v6, uint32_t v7) {
    sts128(a0, plo(v0, v1), plo(v2, v3), plo(v4, v5), plo(v6, v7));
    sts128(a1, phi(v0, v1), phi(v2, v3), phi(v4, v5), phi(v6, v7));
}

__device__ __forceinline__ void wgmma_n128(float (&d)[64], uint32_t a0, uint32_t a1, uint32_t a2, uint32_t a3, uint32_t dlo,
                                           int accumulate) {
    asm volatile("{.reg .pred p; .reg .b64 ds; setp.ne.s32 p,%69,0; mov.b64 ds,{%68,%70};\n"
                 "wgmma.mma_async.sync.aligned.m64n128k16.f32.bf16.bf16 {%0,%1,%2,%3,%4,%5,%6,%7,%8,%9,%10,%11,%12,%13,%14,%15,%16,%17,%18,%19,%20,%21,%22,%23,%24,%25,%26,%27,%28,%29,%30,%31,%32,%33,%34,%35,%36,%37,%38,%39,%40,%41,%42,%43,%44,%45,%46,%47,%48,%49,%50,%51,%52,%53,%54,%55,%56,%57,%58,%59,%60,%61,%62,%63},\n"
                 "{%64,%65,%66,%67},ds,p,1,1,0;}\n"
                 : "+f"(d[0]),"+f"(d[1]),"+f"(d[2]),"+f"(d[3]),"+f"(d[4]),"+f"(d[5]),"+f"(d[6]),"+f"(d[7]),"+f"(d[8]),"+f"(d[9]),"+f"(d[10]),"+f"(d[11]),"+f"(d[12]),"+f"(d[13]),"+f"(d[14]),"+f"(d[15]),"+f"(d[16]),"+f"(d[17]),"+f"(d[18]),"+f"(d[19]),"+f"(d[20]),"+f"(d[21]),"+f"(d[22]),"+f"(d[23]),"+f"(d[24]),"+f"(d[25]),"+f"(d[26]),"+f"(d[27]),"+f"(d[28]),"+f"(d[29]),"+f"(d[30]),"+f"(d[31]),"+f"(d[32]),"+f"(d[33]),"+f"(d[34]),"+f"(d[35]),"+f"(d[36]),"+f"(d[37]),"+f"(d[38]),"+f"(d[39]),"+f"(d[40]),"+f"(d[41]),"+f"(d[42]),"+f"(d[43]),"+f"(d[44]),"+f"(d[45]),"+f"(d[46]),"+f"(d[47]),"+f"(d[48]),"+f"(d[49]),"+f"(d[50]),"+f"(d[51]),"+f"(d[52]),"+f"(d[53]),"+f"(d[54]),"+f"(d[55]),"+f"(d[56]),"+f"(d[57]),"+f"(d[58]),"+f"(d[59]),"+f"(d[60]),"+f"(d[61]),"+f"(d[62]),"+f"(d[63])
                 : "r"(a0), "r"(a1), "r"(a2), "r"(a3), "r"(dlo), "r"(accumulate), "n"(128 >> 4));
}

template <int TS, int KMAX, int LO, int HI, int STRIDE>
__device__ __forceinline__ void toep_block(float (&acc)[4][2][4], const uint32_t (&kb)[KMAX + 1][2][2], uint32_t base,
                                           const uint32_t (&f0)[4], const uint32_t (&f1)[4]) {
    uint32_t fr[4][4];
#pragma unroll
    for (int j = 0; j < 4; ++j) { fr[0][j] = f0[j]; fr[1][j] = f1[j]; }
    if (LO + 2 <= HI) ldsm4t(fr[2], base + (uint32_t)((LO + 2) * STRIDE));
#pragma unroll
    for (int loc = LO; loc <= HI; ++loc) {
        if (loc + 3 <= HI) ldsm4t(fr[(loc + 3 - LO) & 3], base + (loc + 3) * STRIDE);
#pragma unroll
        for (int tj = 0; tj < 4; ++tj) {
            const int ks = TS * tj - loc;
            if (ks >= 0 && ks <= KMAX) {
                mma_bf16(acc[tj][0], fr[(loc - LO) & 3], kb[ks][0][0], kb[ks][0][1]);
                mma_bf16(acc[tj][1], fr[(loc - LO) & 3], kb[ks][1][0], kb[ks][1][1]);
            }
        }
    }
}

__device__ __forceinline__ uint32_t gate_word(float s) {
    float sb = bf_round(s);
    float g = bf_round(1.0f / (1.0f + expf(-sb)));
    float o = bf_round(1.0f - g);
    return ((__float_as_uint(g) >> 16) | (__float_as_uint(o) & 0xFFFF0000u)) & 0x7FFF7FFFu;
}

__device__ __forceinline__ void final_block(const CUtensorMap* tm, uint32_t sb, int cl, int rank, int un, int b, int barid) {
    uint32_t oaddr, obar;
    asm("mapa.shared::cluster.u32 %0,%1,%2;\n" : "=r"(oaddr) : "r"(sb + OFF_OUT + b * 2048 + un * 16), "r"(rank ^ 1));
    asm("mapa.shared::cluster.u32 %0,%1,%2;\n" : "=r"(obar) : "r"(sb + OFF_MB_OUT + 8 * b), "r"(rank ^ 1));
    const uint32_t orow = sb + OFF_ROWS + b * 4096 + (un >> 6) * 2048 + (un & 63) * 16;
    const uint32_t sw = ((2 * un) ^ ((un >> 1) & 0x18)) * 4 + b * 1024;
    const uint32_t psel = rank ? 0x7632u : 0x5410u;
    uint2 ya[4], yb[4];
    const uint4 gw = lds128(sb + OFF_GT + (b * 256 + 2 * un) * 8);
#pragma unroll
    for (int c = 0; c < 4; ++c) {
        ya[c] = lds64(sb + OFF_S1P + c * 8192 + sw);
        yb[c] = lds64(sb + OFF_S1P + c * 8192 + 4096 + sw);
    }
    if (b > 0) {
        mbar_wait(sb + OFF_MB_P + 8 * b);
#pragma unroll
        for (int c = 0; c < 4; ++c) {
            const uint2 za = lds64(sb + OFF_PG2 - 1024 + c * 6144 + sw);
            const uint2 zb = lds64(sb + OFF_PG2 - 1024 + c * 6144 + 3072 + sw);
            ya[c].x = badd2(ya[c].x, za.x); ya[c].y = badd2(ya[c].y, za.y);
            yb[c].x = badd2(yb[c].x, zb.x); yb[c].y = badd2(yb[c].y, zb.y);
        }
    }
    uint32_t o0[4], o1[4];
#pragma unroll
    for (int c = 0; c < 4; ++c) {
        o0[c] = bfma2(ya[c].x, gw.x, bmul2(yb[c].x, gw.y));
        o1[c] = bfma2(ya[c].y, gw.z, bmul2(yb[c].y, gw.w));
    }
    asm volatile("st.async.weak.shared::cluster.mbarrier::complete_tx::bytes.v4.b32 [%0],{%1,%2,%3,%4},[%5];\n"
                 :: "r"(oaddr), "r"(__byte_perm(o0[0], o0[1], psel ^ 0x2222u)), "r"(__byte_perm(o0[2], o0[3], psel ^ 0x2222u)),
                    "r"(__byte_perm(o1[0], o1[1], psel ^ 0x2222u)), "r"(__byte_perm(o1[2], o1[3], psel ^ 0x2222u)),
                    "r"(obar) : "memory");
    sts64(orow + rank * 8, __byte_perm(o0[0], o0[1], psel), __byte_perm(o0[2], o0[3], psel));
    sts64(orow + 1024 + rank * 8, __byte_perm(o1[0], o1[1], psel), __byte_perm(o1[2], o1[3], psel));
    mbar_wait_cluster(sb + OFF_MB_OUT + 8 * b);
    const uint4 pe = lds128(sb + OFF_OUT + b * 2048 + un * 16);
    sts64(orow + 8 - rank * 8, pe.x, pe.y);
    sts64(orow + 1032 - rank * 8, pe.z, pe.w);
    asm volatile("fence.proxy.async.shared::cta;\n" ::: "memory");
    asm volatile("bar.sync %0, 128;\n" :: "r"(barid) : "memory");
    if (un == 0) {
        asm volatile("cp.async.bulk.tensor.4d.global.shared::cta.bulk_group [%0,{%1,%2,%3,%4}],[%5];\n"
                     :: "l"(tm), "r"(8 * cl), "r"(64 * rank), "r"(0), "r"(2 * b), "r"(sb + OFF_ROWS + b * 4096) : "memory");
        asm volatile("cp.async.bulk.commit_group;\n" ::: "memory");
    }
}

__global__ void __cluster_dims__(2, 1, 1) __launch_bounds__(NTHREADS, 1)
fused_s4d_kernel(const __grid_constant__ Params prm, const __grid_constant__ CUtensorMap tm_in,
                 const __grid_constant__ CUtensorMap tm_out) {
    extern __shared__ __align__(1024) unsigned char smem[];
    const uint32_t sb = (uint32_t)__cvta_generic_to_shared(smem);
    const int tid = threadIdx.x, warp = tid >> 5, lane = tid & 31;
    const int rank = blockIdx.x & 1, cl = blockIdx.x >> 1;
    if (warp != 8) asm volatile("barrier.cluster.arrive.relaxed.aligned;\n" ::: "memory");
    STAMP(0);
    if (tid == 128) GSTAMP(0);

    if (warp >= 8) {
        const int un = tid - 256;
        if (warp == 8) {
            if (lane == 0) {
                asm volatile("prefetch.tensormap [%0];\n" :: "l"(&tm_in) : "memory");
                asm volatile("prefetch.tensormap [%0];\n" :: "l"(&tm_out) : "memory");
                mbar_init(sb + OFF_MB_U, 1);
                mbar_init(sb + OFF_MB_P, 16);
#pragma unroll
                for (int i = 1; i < 4; ++i) mbar_init(sb + OFF_MB_P + 8 * i, 4);
#pragma unroll
                for (int i = 0; i < 4; ++i) mbar_init(sb + OFF_MB_OUT + 8 * i, 1);
                mbar_expect(sb + OFF_MB_U, 32768);
#pragma unroll
                for (int i = 0; i < 4; ++i) mbar_expect(sb + OFF_MB_OUT + 8 * i, 2048);
                asm volatile("fence.mbarrier_init.release.cluster;\n" ::: "memory");
                asm volatile("fence.proxy.async.shared::cta;\n" ::: "memory");
            }
            __syncwarp();
            asm volatile("barrier.cluster.arrive.relaxed.aligned;\n" ::: "memory");
        }
        asm volatile("barrier.cluster.wait.acquire.aligned;\n" ::: "memory");
        if (un == 0) {
            asm volatile("cp.async.bulk.tensor.3d.shared::cluster.global.mbarrier::complete_tx::bytes.multicast::cluster "
                         "[%0],[%1,{%2,%3,%4}],[%5],%6;\n"
                         :: "r"(sb + OFF_U + rank * 16384), "l"(&tm_in), "r"(8 * cl), "r"(0), "r"(8 * rank), "r"(sb + OFF_MB_U),
                            "h"((uint16_t)3) : "memory");
        }
        STAMP(9);
        {
            const uint32_t a2 = sb + OFF_SG2 + (warp - 8) * SG2_CH;
            sts128(a2 + (lane < 16 ? G2_W5 : G2_W3) + ((lane & 15) + ((lane >> 3) & 1)) * 16, 0, 0, 0, 0);
            if (lane < 16) sts128(a2 + (lane < 4 ? G2_W9E : lane < 8 ? G2_W9O : lane < 12 ? G2_W7E : G2_W7O) + (lane & 3) * 16, 0, 0, 0, 0);
            sts128(sb + OFF_V + (warp - 8) * V_CH + (lane >> 4) * V_H + (lane & 15) * 16, 0, 0, 0, 0);
        }
        const int g = lane >> 2, q = lane & 3;
        uint32_t epoch = 0;
        if (warp == 8) asm volatile("ld.relaxed.gpu.global.u32 %0,[%1];\n" : "=r"(epoch) : "l"(&g_epoch) : "memory");
        uint4 gx[8], gwv[4];
        const uint4* ur = reinterpret_cast<const uint4*>(prm.u) + (size_t)(blockIdx.x * 16 + g) * 64 + (warp - 8) * 16 + q;
        const uint4* wr = reinterpret_cast<const uint4*>(prm.gw) + (warp - 8) * 16 + q;
#pragma unroll
        for (int j = 0; j < 4; ++j) { gx[2 * j] = __ldg(ur + 4 * j); gx[2 * j + 1] = __ldg(ur + 8 * 64 + 4 * j); gwv[j] = __ldg(wr + 4 * j); }
        {
            float gs[4] = {0.f, 0.f, 0.f, 0.f}, gt[4] = {0.f, 0.f, 0.f, 0.f};
#pragma unroll
            for (int j = 0; j < 4; ++j) {
                uint32_t a[4], b[4];
                a[0] = bmul2(gx[2 * j].x, gwv[j].x); a[1] = bmul2(gx[2 * j + 1].x, gwv[j].x);
                a[2] = bmul2(gx[2 * j].y, gwv[j].y); a[3] = bmul2(gx[2 * j + 1].y, gwv[j].y);
                b[0] = bmul2(gx[2 * j].z, gwv[j].z); b[1] = bmul2(gx[2 * j + 1].z, gwv[j].z);
                b[2] = bmul2(gx[2 * j].w, gwv[j].w); b[3] = bmul2(gx[2 * j + 1].w, gwv[j].w);
                mma_bf16(gs, a, 0x3F803F80u, 0x3F803F80u);
                mma_bf16(gt, b, 0x3F803F80u, 0x3F803F80u);
            }
            if (q == 0) {
                sts32(sb + OFF_GPART + ((warp - 8) * 16 + g) * 4, __float_as_uint(gs[0] + gt[0]));
                sts32(sb + OFF_GPART + ((warp - 8) * 16 + g + 8) * 4, __float_as_uint(gs[2] + gt[2]));
            }
            asm volatile("bar.sync 1, 128;\n" ::: "memory");
            if (warp == 8) {
                const uint32_t tg = (epoch + 1u) & 3u;
                if (lane < 16) {
                    float t = 0.f;
#pragma unroll
                    for (int w = 0; w < 4; ++w) t += __uint_as_float(lds32(sb + OFF_GPART + (w * 16 + lane) * 4));
                    const uint32_t wd = gate_word(t) | ((tg & 1u) << 15) | ((tg & 2u) << 30);
                    asm volatile("st.relaxed.gpu.global.u32 [%0],%1;\n" :: "l"(&g_gate[blockIdx.x * 16 + lane]), "r"(wd) : "memory");
                }
                if (lane == 0) {
                    sts32(sb + OFF_TAG, ((tg & 1u) << 15) | ((tg & 2u) << 30));
                    sts32(sb + OFF_TAG + 4, epoch + 1u);
                }
            }
        }
        STAMP(10);
        mbar_wait(sb + OFF_MB_U);
        STAMP(2);
        const int pi = lane >> 4;
#pragma unroll
        for (int it = 0; it < 2; ++it) {
            const int rho = ((warp - 8) + 4 * it) * 16 + (lane & 15);
            const uint32_t ua = sb + OFF_U + rho * 16 + rank * 8 + pi * 4;
            uint32_t v[16];
#pragma unroll
            for (int j = 0; j < 16; ++j) v[j] = lds32(ua + j * 2048);
            const uint32_t a = sb + OFF_V + (2 * pi) * V_CH + (16 + rho) * 16;
            store_pair(a, a + V_CH, v[0], v[1], v[2], v[3], v[4], v[5], v[6], v[7]);
            store_pair(a + V_H, a + V_H + V_CH, v[8], v[9], v[10], v[11], v[12], v[13], v[14], v[15]);
        }
        asm volatile("fence.proxy.async.shared::cta;\n" ::: "memory");
        asm volatile("bar.arrive 2, 384;\n" ::: "memory");
        STAMP(3);
        asm volatile("bar.sync 9, 384;\n" ::: "memory");
#pragma unroll 1
        for (int it = 0; it < 3; ++it) {
            if (it == 2) {
                asm volatile("bar.arrive 3, 256;\n" ::: "memory");
                STAMP(4);
            }
            const int rho = it * 32 + lane;
            const uint32_t va = sb + OFF_V + (warp - 8) * V_CH + (16 + rho) * 16;
            const uint4 e0 = lds128(va + V_H - 16), e1 = lds128(va), e2 = lds128(va + V_H), e3 = lds128(va + 16);
            const uint32_t E[13] = {e0.z, e0.w, e1.x, e1.y, e1.z, e1.w, e2.x, e2.y, e2.z, e2.w, e3.x, e3.y, e3.z};
            uint32_t O[12], P2[12], W3[12], P4[11], W5[11];
#pragma unroll
            for (int k = 0; k < 12; ++k) { O[k] = __byte_perm(E[k], E[k + 1], 0x5432); P2[k] = badd2(E[k], O[k]); }
#pragma unroll
            for (int k = 1; k < 12; ++k) W3[k] = badd2(O[k - 1], P2[k]);
#pragma unroll
            for (int k = 0; k < 11; ++k) P4[k] = badd2(P2[k], P2[k + 1]);
#pragma unroll
            for (int k = 2; k < 11; ++k) W5[k] = badd2(P4[k - 1], E[k + 1]);
            const uint32_t s2a = sb + OFF_SG2 + (warp - 8) * SG2_CH;
            const int c5 = 2 * rho + 16;
            const uint32_t a5 = s2a + G2_W5 + (c5 + (c5 >> 3)) * 16, a3 = a5 + (G2_W3 - G2_W5);
            sts128(a5, W5[2], W5[3], W5[4], W5[5]); sts128(a5 + 16, W5[6], W5[7], W5[8], W5[9]);
            sts128(a3, W3[4], W3[5], W3[6], W3[7]); sts128(a3 + 16, W3[8], W3[9], W3[10], W3[11]);
            if (it < 2) {
                uint32_t W7[8], W9[8];
#pragma unroll
                for (int k = 0; k < 8; ++k) { W7[k] = badd2(W3[k + 1], P4[k + 2]); W9[k] = badd2(P4[k], W5[k + 3]); }
                const uint32_t a9 = s2a + (rho + 4) * 16, ap = s2a + rho * 16;
                sts128(a9 + G2_W9E, W9[0], W9[1], W9[2], W9[3]); sts128(a9 + G2_W9O, W9[4], W9[5], W9[6], W9[7]);
                sts128(a9 + G2_W7E, W7[0], W7[1], W7[2], W7[3]); sts128(a9 + G2_W7O, W7[4], W7[5], W7[6], W7[7]);
                sts128(ap + G2_P2E, P2[0], P2[1], P2[2], P2[3]); sts128(ap + G2_P2O, P2[4], P2[5], P2[6], P2[7]);
                if (rho == 0) {
                    const uint32_t n12 = plo(E[2], P2[2]);
                    sts128(a5 - 32, 0, 0, 0, n12);
                    sts128(a3 - 32, 0, W3[1], W3[2], W3[3]);
                    sts128(a9 + G2_W9O - 16, 0, 0, n12, __byte_perm(W3[2], P4[2], 0x5432));
                    sts128(a9 + G2_W7O - 16, 0, 0, E[2] << 16, __byte_perm(P2[2], W3[2], 0x7610));
                }
            }
        }
        asm volatile("bar.arrive 4, 256;\n" ::: "memory");
        {
            const int uc = un;
            const uint32_t tagw = lds32(sb + OFF_TAG);
            bool done = false;
            const int tb0 = (uc >> 5) * 256 + (uc & 31) * 4;
#pragma unroll 1
            for (int tries = 0; tries < 8192 && !done; ++tries) {
                uint4 v[4];
#pragma unroll
                for (int i = 0; i < 4; ++i)
                    asm volatile("ld.relaxed.gpu.global.v4.u32 {%0,%1,%2,%3},[%4];\n"
                                 : "=r"(v[i].x), "=r"(v[i].y), "=r"(v[i].z), "=r"(v[i].w)
                                 : "l"(&g_gate[tb0 + (i >> 1) * 1024 + (i & 1) * 128]) : "memory");
                uint32_t bad = 0;
#pragma unroll
                for (int i = 0; i < 4; ++i)
                    bad |= (v[i].x ^ tagw) | (v[i].y ^ tagw) | (v[i].z ^ tagw) | (v[i].w ^ tagw);
                done = __all_sync(0xffffffffu, (bad & 0x80008000u) == 0);
                if (done) {
#pragma unroll
                    for (int i = 0; i < 2; ++i) {
                        const uint4 a = v[2 * i], b = v[2 * i + 1];
                        const uint32_t d = sb + OFF_GT + (i * 512 + uc * 4) * 8;
                        sts128(d, plo(a.x, b.x) & 0x7FFF7FFFu, phi(a.x, b.x) & 0x7FFF7FFFu, plo(a.y, b.y) & 0x7FFF7FFFu, phi(a.y, b.y) & 0x7FFF7FFFu);
                        sts128(d + 16, plo(a.z, b.z) & 0x7FFF7FFFu, phi(a.z, b.z) & 0x7FFF7FFFu, plo(a.w, b.w) & 0x7FFF7FFFu, phi(a.w, b.w) & 0x7FFF7FFFu);
                    }
                } else {
                    __nanosleep(64);
                }
            }
            if (!done) {
#pragma unroll 1
                for (int k = 0; k < 512; ++k) {
                    const int t = (k >> 8) * 1024 + (uc >> 5) * 256 + (k & 255);
                    float s = 0.f;
#pragma unroll 1
                    for (int j = 0; j < 8; ++j) {
                        const uint32_t pr = bmul2(reinterpret_cast<const uint32_t*>(prm.u)[t * 256 + j * 32 + lane],
                                                  reinterpret_cast<const uint32_t*>(prm.gw)[j * 32 + lane]);
                        s += bf_lo(pr) + bf_hi(pr);
                    }
#pragma unroll
                    for (int o = 16; o > 0; o >>= 1) s += __shfl_xor_sync(0xffffffffu, s, o);
                    if (lane == 0) {
                        const uint32_t wd = gate_word(s);
                        const uint32_t d = sb + OFF_GT + ((t >> 8) * 128 + (t & 127)) * 8 + ((t >> 7) & 1) * 2;
                        asm volatile("st.shared.u16 [%0],%1;\n" :: "r"(d), "h"((uint16_t)(wd & 0xFFFFu)) : "memory");
                        asm volatile("st.shared.u16 [%0],%1;\n" :: "r"(d + 4), "h"((uint16_t)(wd >> 16)) : "memory");
                    }
                }
            }
        }
        asm volatile("bar.sync 1, 128;\n" ::: "memory");
        STAMP(11);
        if (un == 32) {
            asm volatile("{.reg .pred p; .reg .u32 n;\n"
                         "atom.relaxed.gpu.global.inc.u32 n,[%0],%2;\n"
                         "setp.eq.u32 p,n,%2;\n"
                         "@p st.relaxed.gpu.global.u32 [%1],%3;}\n"
                         :: "l"(&g_arrived), "l"(&g_epoch), "r"(gridDim.x - 1), "r"(lds32(sb + OFF_TAG + 4)) : "memory");
        }
        __syncwarp();
        asm volatile("bar.arrive 10, 256;\n" ::: "memory");
        mbar_wait(sb + OFF_MB_P);
#pragma unroll 1
        for (int b = 0; b < 4; b += (b == 1) ? 2 : 1) {
            final_block(&tm_out, sb, cl, rank, un, b, 1);
            STAMP(5 + b);
        }
        if (un == 0) {
            asm volatile("cp.async.bulk.wait_group.read 0;\n" ::: "memory");
            STAMP(13);
            GSTAMP(1);
        }
        return;
    }

    const int ch = warp & 3, role = warp >> 2;
    const int chg = 8 * cl + 4 * rank + ch;
    const int g = lane >> 2, q = lane & 3;

    uint2 pLA, pAI, pCR, pCI;
    {
        const size_t o = (size_t)chg * 128 + lane * 4;
        pLA = __ldg(reinterpret_cast<const uint2*>(prm.p[role][0] + o));
        pAI = __ldg(reinterpret_cast<const uint2*>(prm.p[role][1] + o));
        pCR = __ldg(reinterpret_cast<const uint2*>(prm.p[role][2] + o));
        pCI = __ldg(reinterpret_cast<const uint2*>(prm.p[role][3] + o));
    }
    const float log_dt = __bfloat162float(prm.p[role][4][chg]);
    const float dskip = __bfloat162float(prm.p[role][5][chg]);

    const uint32_t kt = sb + OFF_KT + warp * KT_W;
    {
        if (lane < 30) sts64(kt + KT_WD1 + (lane < 14 ? lane : 258 + lane) * 8, 0u, 0u);
        const uint32_t z2 = kt + KT_WD4 + (lane < 7 ? lane : 64 + lane) * 4;
        if (lane < 16) { sts32(z2, 0u); sts32(z2 + 320, 0u); }
    }
    float dt = 0.f, fscale = 0.f, cinv = 0.f, f0 = 0.f;
    float dk[5][4];
#pragma unroll
    for (int j = 0; j < 5; ++j) { dk[j][0] = dk[j][1] = dk[j][2] = dk[j][3] = 0.f; }
    {
        const uint32_t tb = sb + OFF_FT + warp * FT_W;
        const int mat = lane >> 3, rr = lane & 7;
        const uint32_t stb = tb + (71 * rr + 8 * (mat & 1)) * 16, stc = tb + (71 * rr + 64 + (mat & 1)) * 16;
        const uint32_t ld0 = tb + ((mat & 1) ? 64 + (mat >> 1) : 8 * (mat >> 1) + rr) * 16;
        const uint32_t ld1 = tb + (16 + 8 * mat + rr) * 16;
        const uint32_t ld2 = tb + ((mat & 2) ? 64 + mat : 48 + 8 * mat + rr) * 16;
        const uint32_t ld3 = tb + (71 * (mat >> 1) + 68 + (mat & 1)) * 16;
#pragma unroll
        for (int r = 0; r < 2; ++r) {
            uint32_t wLA = 0u, wAI = 0u, wCR = 0u, wCI = 0u;
            if (r == 0) {
                dt = bf_round(expf(log_dt));
                uint32_t m = max(max(max(pCR.x & 0x7F80u, (pCR.x >> 16) & 0x7F80u), max(pCR.y & 0x7F80u, (pCR.y >> 16) & 0x7F80u)),
                                 max(max(pCI.x & 0x7F80u, (pCI.x >> 16) & 0x7F80u), max(pCI.y & 0x7F80u, (pCI.y >> 16) & 0x7F80u)));
                m = __reduce_max_sync(0xffffffffu, m) >> 7;
                m = min(max(m, 1u), 253u);
                cinv = __uint_as_float((254u - m) << 23);
                fscale = 2.0f * dt * __uint_as_float(m << 23);
                wLA = pLA.x; wAI = pAI.x; wCR = pCR.x; wCI = pCI.x;
                STAMP(1);
            } else if (r == 1) {
                f0 = (bf_lo(pCR.x) + bf_hi(pCR.x)) + (bf_lo(pCR.y) + bf_hi(pCR.y));
#pragma unroll
                for (int o = 16; o > 0; o >>= 1) f0 += __shfl_xor_sync(0xffffffffu, f0, o);
                f0 = fmaf(2.0f * dt, f0, dskip);
                wLA = pLA.y; wAI = pAI.y; wCR = pCR.y; wCI = pCI.y;
            }
            float ea, eb;
            asm("ex2.approx.ftz.f32 %0,%1;\n" : "=f"(ea) : "f"(bf_lo(wLA) * 1.4426950408889634f));
            asm("ex2.approx.ftz.f32 %0,%1;\n" : "=f"(eb) : "f"(bf_hi(wLA) * 1.4426950408889634f));
            const uint32_t e2 = pack_bf16(ea, eb);
            const float ala = (-bf_lo(e2) * dt) * 1.4426950408889634f, alb = (-bf_hi(e2) * dt) * 1.4426950408889634f;
            const float aia = bf_lo(wAI) * dt, aib = bf_hi(wAI) * dt;
            const pc C = mk64(pack_f16(bf_lo(wCR) * cinv, bf_hi(wCR) * cinv), pack_f16(bf_lo(wCI) * cinv, bf_hi(wCI) * cinv));
            {
                c32 a = cexp_seed(ala, -aia, 16.f), b = cexp_seed(alb, -aib, 16.f);
                const pc f1 = mkp(a, b); a = csq(a); b = csq(b);
                const pc f2 = mkp(a, b); a = csq(a); b = csq(b);
                const pc f4 = mkp(a, b); a = csq(a); b = csq(b);
                stp(stb, 0x3C003C00ull);
                stp(stb + 16, f1); stp(stb + 32, f2); stp(stb + 64, f4); stp(stc, mkp(a, b));
                const pc f3 = pmul(f1, f2);
                stp(stb + 48, f3); stp(stb + 80, pmul(f1, f4)); stp(stb + 96, pmul(f2, f4)); stp(stb + 112, pmul(f3, f4));
                a = cexp_seed(ala, aia, 1.f); b = cexp_seed(alb, aib, 1.f);
                const pc w1 = mkp(a, b); a = csq(a); b = csq(b);
                const pc w2 = mkp(a, b); a = csq(a); b = csq(b);
                const pc w4 = mkp(a, b); a = csq(a); b = csq(b);
                const pc w8 = mkp(a, b);
                stp(stc + 32, w1);
                pc D[4];
                D[0] = pmul(C, w1); D[1] = pmul(D[0], w2); D[2] = pmul(D[0], w4); D[3] = pmul(D[1], w4);
#pragma unroll
                for (int j = 0; j < 4; ++j) { stp(stb + 256 + 16 * j, D[j]); stp(stb + 320 + 16 * j, pmul(D[j], w8)); }
                a = cexp_seed(ala, aia, 256.f); b = cexp_seed(alb, aib, 256.f);
                const pc w256 = mkp(a, b); a = csq(a); b = csq(b);
                const pc w512 = mkp(a, b); a = csq(a); b = csq(b);
                const pc w1024 = mkp(a, b);
                stp(stc + 64, w256);
                D[0] = pmul(C, w4); D[1] = pmul(C, w8); D[2] = pmul(D[0], w8); D[3] = pmul(D[1], w8);
#pragma unroll
                for (int j = 0; j < 4; ++j) {
                    const pc t = pmul(D[j], w512);
                    stp(stb + 512 + 16 * j, t); stp(stb + 576 + 16 * j, pmul(t, w256));
                }
#pragma unroll
                for (int j = 0; j < 2; ++j) {
                    const pc t = pmul(D[2 * j + 1], w1024), t2 = pmul(t, w256);
                    stp(stb + 768 + 16 * j, t); stp(stb + 800 + 16 * j, t2);
                    stp(stb + 832 + 16 * j, pmul(t, w512)); stp(stb + 864 + 16 * j, pmul(t2, w512));
                }
            }
            __syncwarp();
#pragma unroll
            for (int s = 0; s < 8; s += 2) {
                uint32_t W[4];
                ldsm4(W, ld3 + s * 1136);
#pragma unroll
                for (int h = 0; h < 2; ++h) {
                    uint32_t L0[4], L1[4], L2[4];
                    ldsm4(L0, ld0 + (s + h) * 1136); ldsm4(L1, ld1 + (s + h) * 1136); ldsm4(L2, ld2 + (s + h) * 1136);
                    uint32_t A[4];
                    A[0] = L0[0]; A[2] = L0[2];
                    asm("{.reg .b32 t0,t1,n; mul.rn.f16x2 t0,%2,%4; mul.rn.f16x2 t1,%3,%4; neg.f16x2 n,%3;\n"
                        "fma.rn.f16x2 %0,n,%5,t0; fma.rn.f16x2 %1,%2,%5,t1;}\n"
                        : "=r"(A[1]), "=r"(A[3]) : "r"(L0[0]), "r"(L0[2]), "r"(L0[1]), "r"(L0[3]));
                    const pc t1 = pmul(mk64(L1[0], L1[1]), mk64(L2[2], L2[3]));
                    const pc t2 = pmul(t1, mk64(W[2 * h], W[2 * h + 1]));
                    mma_f16(dk[0], A, L1[0], L1[1]);
                    mma_f16(dk[3], A, L1[2], L1[3]);
                    mma_f16(dk[4], A, L2[0], L2[1]);
                    mma_f16p(dk[1], A, t1);
                    mma_f16p(dk[2], A, t2);
                }
            }
            __syncwarp();
        }
    }
    STAMP(2);

    {
        const bool last = (lane == 31);
#pragma unroll
        for (int j = 0; j < 5; ++j)
#pragma unroll
            for (int c = 0; c < 4; ++c) dk[j][c] *= fscale;
        const float f256 = dk[1][3], f512 = dk[2][3], f1024 = dk[3][3];
        if (last) { dk[2][2] -= f512; dk[2][3] = 0.f; }
        const float n0 = __shfl_sync(0xffffffffu, dk[0][0], (lane + 1) & 31), n1 = __shfl_sync(0xffffffffu, dk[0][2], (lane + 1) & 31);
        const float p0 = __shfl_sync(0xffffffffu, lane == 31 ? f256 : dk[2][1], (lane + 31) & 31);
        const float p1 = __shfl_sync(0xffffffffu, lane == 31 ? dk[2][1] : dk[2][3], (lane + 31) & 31);
#pragma unroll
        for (int hh = 0; hh < 2; ++hh) {
            const float a = dk[0][2 * hh], b = dk[1][2 * hh], c = dk[0][2 * hh + 1], d = dk[1][2 * hh + 1];
            const float an = hh == 0 ? (last ? n1 : n0) : (last ? d : n1);
            const uint32_t wa = kt + KT_WD1 + (16 + 4 * lane + 128 * hh) * 8;
            const float be = dk[2][2 * hh], al = dk[2][2 * hh + 1];
            const uint32_t aa = pack_bf16(al, al);
            const uint32_t w0 = pack_bf16(b, a), w1 = pack_bf16(c, b), w2 = pack_bf16(d, c), w3 = pack_bf16(an, d);
            sts128(wa, w0, pack_bf16(be, hh == 0 ? p0 : p1), w1, pack_bf16(al, be));
            sts128(wa + 16, w2, aa, w3, aa);
            if (hh == 1 && lane >= 28) {
                sts32(wa - 2048 + 4, w0); sts32(wa - 2048 + 12, w1); sts32(wa - 2048 + 20, w2); sts32(wa - 2048 + 28, w3);
            }
        }
        if (lane == 0) { sts32(kt + KT_WD1 + 14 * 8, pack_bf16(f0, 0.f)); sts32(kt + KT_WD1 + 15 * 8, pack_bf16(dk[0][0], f0)); }
#pragma unroll
        for (int hh = 0; hh < 2; ++hh) {
            const int i = g + 8 * hh;
            sts32(kt + KT_WD4 + (2 * i + (q & 1) + 32 * (q >> 1) + 8) * 4, pack_bf16(dk[3][2 * hh + 1], dk[3][2 * hh]));
            sts32(kt + KT_WD4 + 320 + (i + 16 * q + 7) * 4, pack_bf16(dk[4][2 * hh + 1], dk[4][2 * hh]));
        }
        if (last) {
            const uint32_t w512 = pack_bf16(f512, 0.f);
            sts32(kt + KT_WD4 + 7 * 4, w512);
            sts128(kt + KT_WD1 + 274 * 8, w512, 0u, w512, 0u);
            sts32(kt + KT_FIX, pack_bf16(f1024, f1024));
        }
    }
    STAMP(3);
    asm volatile("bar.sync 2, 384;\n" ::: "memory");
    STAMP(6);

    const uint32_t ktA = sb + OFF_KT + ch * KT_W, ktB = ktA + 4 * KT_W;
    const int mat = lane >> 3, rr = lane & 7;
    const int np = 4 * (g & 1) + (g >> 1);
    uint32_t k4[9][2][2], k8[8][2][2], kf[2];
    const uint32_t o4 = KT_WD4 + (g - q + 7) * 4;
    const uint32_t o8 = KT_WD4 + 320 + (np + 7 - q) * 4;
#define K_LOAD(DST, OFF, KS)                                                                                 \
        { DST[KS][0][0] = lds32(ktA + OFF + (8 * (KS)) * 4); DST[KS][0][1] = lds32(ktA + OFF + (8 * (KS) - 4) * 4); \
          DST[KS][1][0] = lds32(ktB + OFF + (8 * (KS)) * 4); DST[KS][1][1] = lds32(ktB + OFF + (8 * (KS) - 4) * 4); }
    {
        const int rb = ch >> 1, br = ch & 1;
        const int urole = __shfl_sync(0xffffffffu, role, 0);
        uint32_t wa = sb + OFF_KT + (br * 4 + role) * KT_W + KT_WD1 + (14 + 8 * rb + g - 2 * q) * 8;
        uint2 af[17][2];
#define A_LOAD(S)                                                                                            \
        if ((S) < 16) { af[S][0] = lds64(wa + 128 * (S)); af[S][1] = lds64(wa + 128 * (S) - 64); }           \
        else { af[S][0] = make_uint2(0u, lds32(wa + 128 * (S) + 4)); af[S][1] = make_uint2(0u, lds32(wa + 128 * (S) - 60)); }
        if (urole) asm volatile("bar.sync 9, 384;\n" ::: "memory");
#pragma unroll
        for (int s = 0; s < 9; ++s) { A_LOAD(s) }
#pragma unroll 1
        for (int cc = 0; cc < 2; ++cc) {
#pragma unroll
            for (int s = 9; s < 17; ++s) { A_LOAD(s) }
            const int c = urole + 2 * cc;
            const uint32_t desc = (((sb + OFF_V + c * V_CH + 256) & 0x3FFFFu) >> 4) | ((V_H >> 4) << 16);
            float d[64];
            if (urole | cc) asm volatile("bar.sync %0, 256;\n" :: "r"(5 + urole) : "memory");
            else asm volatile("bar.arrive 9, 384;\n" ::: "memory");
            asm volatile("wgmma.fence.sync.aligned;\n" ::: "memory");
#pragma unroll
            for (int s = 0; s < 9; ++s) wgmma_n128(d, af[s][0].x, af[s][0].y, af[s][1].x, af[s][1].y, desc - s, s);
            asm volatile("wgmma.commit_group.sync.aligned;\n" ::: "memory");
#pragma unroll
            for (int s = 9; s < 17; ++s)
                wgmma_n128(d, af[s][0].x, af[s][0].y, af[s][1].x, af[s][1].y, desc - s, 1);
            asm volatile("wgmma.commit_group.sync.aligned;\n" ::: "memory");
            if (!(urole & cc)) asm volatile("bar.arrive %0, 256;\n" :: "r"(6 - urole) : "memory");
            asm volatile("wgmma.wait_group.sync.aligned 1;\n" ::: "memory");
            wa += 2 * KT_W;
            if (cc == 0) {
#pragma unroll
                for (int s = 0; s < 9; ++s) { A_LOAD(s) }
            }
            asm volatile("wgmma.wait_group.sync.aligned 0;\n" ::: "memory");
#pragma unroll
            for (int i = 0; i < 64; ++i) asm volatile("" : "+f"(d[i]) :: "memory");
            if (urole & cc) asm volatile("bar.arrive 7, 256;\n" ::: "memory");
            if (cc == 0) STAMP(4); else STAMP(5);
            if (rb == 1 && (lane | 4) == 31) {
                const uint32_t u01 = lds32(sb + OFF_V + c * V_CH + 256);
                const float f512 = bf_lo(lds32(wa - 2 * KT_W + 252 * 8));
                d[13] = fmaf(f512, lane == 27 ? bf_lo(u01) : bf_lo(u01) + bf_hi(u01), d[13]);
            }
            const uint32_t dst = sb + OFF_S1P + c * 8192 + br * 4096 + (32 * q + g) * 4;
#pragma unroll
            for (int j = 0; j < 16; j += 2)
#pragma unroll
                for (int e = 0; e < 2; ++e) {
                    const float y0 = j >= 2 ? d[4 * j + e] + d[4 * j - 6 + e] : d[4 * j + e];
                    const float y1 = j >= 2 ? d[4 * j + 4 + e] + d[4 * j - 2 + e] : d[4 * j + 4 + e];
                    sts32(dst + j * 256 + ((16 * e + 8 * rb) ^ (8 * q)) * 4, pack_bf16(y0, y1));
                }
            __syncwarp();
            if (lane == 0) mbar_arrive(sb + OFF_MB_P);
        }
#undef A_LOAD
    }
    STAMP(7);

    {
        const uint32_t s2 = sb + OFF_SG2 + ch * SG2_CH;
        const uint32_t b4 = s2 + ((rr & 1) ? G2_W3 : G2_W5) + (18 + 9 * (mat & 1) + 4 * (mat >> 1) + (rr >> 1)) * 16;
        const int d8 = 6 + 8 * (mat >> 1) + rr + (mat & 1);
        const uint32_t b8 = s2 + ((rr & 1) ? ((d8 & 1) ? G2_W7O : G2_W7E) : ((d8 & 1) ? G2_W9O : G2_W9E)) + (d8 >> 1) * 16;
        const uint32_t bf = s2 + ((mat & 1) ? G2_P2O : G2_P2E) + rr * 16;
        const uint32_t pg = sb + OFF_PG2 + ch * 6144 + (32 * (q >> 1) + g) * 4;
        const int blk = 2 + role;
        const uint32_t c8 = b8 + (4 * blk - 8) * 128, c4 = b4 + (8 * blk - 8) * 144;
#define G2_STORE(ACC, BLK)                                                                                   \
        _Pragma("unroll") for (int tj = 0; tj < 4; tj += 2)                                                  \
            _Pragma("unroll") for (int br = 0; br < 2; ++br)                                                 \
                _Pragma("unroll") for (int c = 0; c < 4; ++c)                                                \
                    sts32(pg + br * 3072 + ((BLK) - 1) * 1024 + tj * 256 + (c >> 1) * 256 +                  \
                          (16 * ((q & 1) ^ (c >> 1)) + 8 * ((c & 1) ^ (q >> 1))) * 4,                        \
                          pack_bf16(ACC[tj][br][c], ACC[tj + 1][br][c]));                                    \
        __syncwarp();                                                                                         \
        if (lane == 0) mbar_arrive(sb + OFF_MB_P + 8 * (BLK));
        uint32_t fa[4], fb[4], fc[4], fd[4], fx[4][2];
#pragma unroll
        for (int ks = 0; ks < 9; ++ks) K_LOAD(k4, o4, ks);
        {
            const uint32_t msk = ((np >> 1) == q) ? ((np & 1) ? 0xFFFF0000u : 0x0000FFFFu) : 0u;
            kf[0] = lds32(ktA + KT_FIX) & msk; kf[1] = lds32(ktB + KT_FIX) & msk;
        }
#pragma unroll
        for (int ks = 0; ks < 4; ++ks) K_LOAD(k8, o8, ks);
        if (role) {
#pragma unroll
            for (int ks = 4; ks < 8; ++ks) K_LOAD(k8, o8, ks);
        }
        asm volatile("bar.sync %0, 256;\n" :: "r"(3 + role) : "memory");
        STAMP(8);
        float a8[4][2][4];
#pragma unroll
        for (int tj = 0; tj < 4; ++tj)
#pragma unroll
            for (int br = 0; br < 2; ++br) { a8[tj][br][0] = a8[tj][br][1] = a8[tj][br][2] = a8[tj][br][3] = 0.f; }
        if (role == 0) {
            ldsm4t(fa, b4 - 2 * 144); ldsm4t(fb, b4 - 144);
            asm volatile("bar.sync 7, 256;\n" ::: "memory");
            float a1[4][2][4];
#pragma unroll
            for (int tj = 0; tj < 4; ++tj)
#pragma unroll
                for (int br = 0; br < 2; ++br) { a1[tj][br][0] = a1[tj][br][1] = a1[tj][br][2] = a1[tj][br][3] = 0.f; }
            toep_block<2, 8, -2, 6, 144>(a1, k4, b4, fa, fb);
            G2_STORE(a1, 1);
            STAMP(9);
        } else {
            ldsm4t(fc, b8); ldsm4t(fd, b8 + 128);
            toep_block<1, 7, -4, -1, 128>(a8, k8, b8 + 4 * 128, fc, fd);
        }
#pragma unroll
        for (int tj = 0; tj < 4; ++tj) ldsm2t(fx[tj][0], fx[tj][1], bf + (4 * blk - 8 + tj) * 128);
        ldsm4t(fc, c8); ldsm4t(fd, c8 + 128);
        ldsm4t(fa, c4 - 8 * 144); ldsm4t(fb, c4 - 7 * 144);
#pragma unroll
        for (int tj = 0; tj < 4; ++tj) { mma_bf16_k8(a8[tj][0], fx[tj][0], fx[tj][1], kf[0]); mma_bf16_k8(a8[tj][1], fx[tj][0], fx[tj][1], kf[1]); }
        toep_block<1, 7, 0, 3, 128>(a8, k8, c8, fc, fd);
        float a4[4][2][4];
#pragma unroll
        for (int tj = 0; tj < 4; ++tj)
#pragma unroll
            for (int br = 0; br < 2; ++br) {
                a4[tj][br][0] = a8[tj][br][0]; a4[tj][br][1] = a8[tj][br][2];
                a4[tj][br][2] = a8[tj][br][1]; a4[tj][br][3] = a8[tj][br][3];
            }
        toep_block<2, 8, -8, 6, 144>(a4, k4, c4, fa, fb);
        G2_STORE(a4, blk);
        STAMP(10);
#undef G2_STORE
#undef K_LOAD
    }
    asm volatile("barrier.cluster.wait.acquire.aligned;\n" ::: "memory");
    if (role == 0) {
        asm volatile("bar.sync 10, 256;\n" ::: "memory");
        mbar_wait(sb + OFF_MB_P);
        final_block(&tm_out, sb, cl, rank, tid, 2, 11);
        STAMP(11);
        if (tid == 0) asm volatile("cp.async.bulk.wait_group.read 0;\n" ::: "memory");
    }
}

typedef CUresult (*EncodeFn)(CUtensorMap*, CUtensorMapDataType, cuuint32_t, void*, const cuuint64_t*, const cuuint64_t*,
                             const cuuint32_t*, const cuuint32_t*, CUtensorMapInterleave, CUtensorMapSwizzle,
                             CUtensorMapL2promotion, CUtensorMapFloatOOBfill);

}

extern "C" void kernel_launch(void* const* d_in, const int* in_sizes, int n_in, void* d_out, int out_size) {
    (void)in_sizes; (void)n_in; (void)out_size;
    static EncodeFn encode = nullptr;
    if (!encode) {
        void* fn = nullptr;
        cudaDriverEntryPointQueryResult qr;
        cudaGetDriverEntryPoint("cuTensorMapEncodeTiled", &fn, cudaEnableDefault, &qr);
        encode = (EncodeFn)fn;
        cudaFuncSetAttribute(fused_s4d_kernel, cudaFuncAttributeMaxDynamicSharedMemorySize, SMEM_BYTES);
    }
    CUtensorMap tin, tout;
    {
        cuuint64_t gd[3] = {DCH, 128, 16};
        cuuint64_t gs[2] = {16 * 1024, 1024};
        cuuint32_t bx[3] = {8, 128, 8};
        cuuint32_t es[3] = {1, 1, 1};
        encode(&tin, CU_TENSOR_MAP_DATA_TYPE_BFLOAT16, 3, d_in[0], gd, gs, bx, es, CU_TENSOR_MAP_INTERLEAVE_NONE,
               CU_TENSOR_MAP_SWIZZLE_NONE, CU_TENSOR_MAP_L2_PROMOTION_NONE, CU_TENSOR_MAP_FLOAT_OOB_FILL_NONE);
    }
    {
        cuuint64_t gd[4] = {DCH, 128, 2, 8};
        cuuint64_t gs[3] = {2048, 1024, 256 * 1024};
        cuuint32_t bx[4] = {8, 64, 2, 2};
        cuuint32_t es[4] = {1, 1, 1, 1};
        encode(&tout, CU_TENSOR_MAP_DATA_TYPE_BFLOAT16, 4, d_out, gd, gs, bx, es, CU_TENSOR_MAP_INTERLEAVE_NONE,
               CU_TENSOR_MAP_SWIZZLE_NONE, CU_TENSOR_MAP_L2_PROMOTION_NONE, CU_TENSOR_MAP_FLOAT_OOB_FILL_NONE);
    }
    Params prm;
    prm.u = (const __nv_bfloat16*)d_in[0];
    for (int j = 0; j < 6; ++j) {
        prm.p[0][j] = (const __nv_bfloat16*)d_in[1 + j];
        prm.p[1][j] = (const __nv_bfloat16*)d_in[8 + j];
    }
    prm.gw = (const __nv_bfloat16*)d_in[14];
    fused_s4d_kernel<<<128, NTHREADS, SMEM_BYTES, cudaStreamPerThread>>>(prm, tin, tout);
}
```

```cpp
#include <cuda_runtime.h>
#include <cuda_bf16.h>
#include <cuda_fp16.h>
#include <cuda.h>
#include <stdint.h>

#define PROFILE_CLK 0

namespace {

constexpr int LSEQ = 2048;
constexpr int DCH = 512;
constexpr int NTHREADS = 384;

constexpr int OFF_U = 0;
constexpr int OFF_ROWS = OFF_U;
constexpr int G2_W5 = 0, G2_W3 = 3776, G2_W9E = 7552, G2_W9O = G2_W9E + 1152, G2_W7E = G2_W9O + 1152 + 48,
              G2_W7O = G2_W7E + 1152 + 16, G2_P2E = G2_W7O + 1088 + 64, G2_P2O = G2_P2E + 1024, SG2_CH = 14336;
static_assert((G2_W7O - G2_W9E) % 128 == 64 && (G2_W7E + 16 - G2_W9O) % 128 == 64 && G2_P2O + 1024 <= SG2_CH, "banks");
constexpr int OFF_SG2 = 32768;
constexpr int V_H = 144 * 16, V_CH = 2 * V_H;
constexpr int OFF_V = OFF_SG2 + 4 * SG2_CH;
constexpr int OFF_S1P = OFF_V + 4 * V_CH;
constexpr int OFF_PG2 = OFF_S1P + 32768;
constexpr int OFF_GT = OFF_PG2 + 24576;
constexpr int FT_W = 8 * 71 * 16;
constexpr int OFF_FT = OFF_S1P;
constexpr int KT_W = 2960;
constexpr int KT_WD1 = 0, KT_WD4 = 288 * 8, KT_FIX = KT_WD4 + 2 * 320;
constexpr int OFF_KT = OFF_FT + 8 * FT_W;
constexpr int OFF_OUT = OFF_KT + 8 * KT_W;
constexpr int OFF_MISC = OFF_OUT + 8192;
constexpr int OFF_MB_U = OFF_MISC, OFF_MB_P = OFF_MISC + 8, OFF_MB_OUT = OFF_MISC + 40;
constexpr int OFF_TAG = OFF_MISC + 72;
constexpr int OFF_GPART = OFF_MISC + 128;
constexpr int SMEM_BYTES = OFF_GPART + 256;
static_assert(OFF_V % 128 == 0 && OFF_S1P % 128 == 0 && OFF_KT % 128 == 0 && OFF_OUT % 128 == 0, "align");
static_assert(OFF_GT + 8192 <= OFF_KT && KT_FIX + 4 <= KT_W && SMEM_BYTES <= 232448, "smem");

struct Params {
    const __nv_bfloat16* u;
    const __nv_bfloat16* p[2][6];
    const __nv_bfloat16* gw;
};

__device__ __align__(128) uint32_t g_gate[LSEQ];
__device__ uint32_t g_epoch;
__device__ uint32_t g_arrived;
#define STAMP(i) do {} while (0)
#define GSTAMP(i) do {} while (0)

__device__ __forceinline__ void ldsm4(uint32_t (&r)[4], uint32_t a) {
    asm volatile("ldmatrix.sync.aligned.m8n8.x4.shared.b16 {%0,%1,%2,%3},[%4];\n"
                 : "=r"(r[0]), "=r"(r[1]), "=r"(r[2]), "=r"(r[3]) : "r"(a) : "memory");
}
__device__ __forceinline__ void ldsm4t(uint32_t (&r)[4], uint32_t a) {
    asm volatile("ldmatrix.sync.aligned.m8n8.x4.trans.shared.b16 {%0,%1,%2,%3},[%4];\n"
                 : "=r"(r[0]), "=r"(r[1]), "=r"(r[2]), "=r"(r[3]) : "r"(a) : "memory");
}
__device__ __forceinline__ void ldsm2t(uint32_t& r0, uint32_t& r1, uint32_t a) {
    asm volatile("ldmatrix.sync.aligned.m8n8.x2.trans.shared.b16 {%0,%1},[%2];\n" : "=r"(r0), "=r"(r1) : "r"(a) : "memory");
}
__device__ __forceinline__ void mma_bf16(float (&d)[4], const uint32_t (&a)[4], uint32_t b0, uint32_t b1) {
    asm("mma.sync.aligned.m16n8k16.row.col.f32.bf16.bf16.f32 {%0,%1,%2,%3},{%4,%5,%6,%7},{%8,%9},{%0,%1,%2,%3};\n"
        : "+f"(d[0]), "+f"(d[1]), "+f"(d[2]), "+f"(d[3])
        : "r"(a[0]), "r"(a[1]), "r"(a[2]), "r"(a[3]), "r"(b0), "r"(b1));
}
__device__ __forceinline__ void mma_bf16_k8(float (&d)[4], uint32_t a0, uint32_t a1, uint32_t b0) {
    asm("mma.sync.aligned.m16n8k8.row.col.f32.bf16.bf16.f32 {%0,%1,%2,%3},{%4,%5},{%6},{%0,%1,%2,%3};\n"
        : "+f"(d[0]), "+f"(d[1]), "+f"(d[2]), "+f"(d[3]) : "r"(a0), "r"(a1), "r"(b0));
}
__device__ __forceinline__ void mma_f16(float (&d)[4], const uint32_t (&a)[4], uint32_t b0, uint32_t b1) {
    asm("mma.sync.aligned.m16n8k16.row.col.f32.f16.f16.f32 {%0,%1,%2,%3},{%4,%5,%6,%7},{%8,%9},{%0,%1,%2,%3};\n"
        : "+f"(d[0]), "+f"(d[1]), "+f"(d[2]), "+f"(d[3])
        : "r"(a[0]), "r"(a[1]), "r"(a[2]), "r"(a[3]), "r"(b0), "r"(b1));
}
__device__ __forceinline__ uint32_t lds32(uint32_t a) {
    uint32_t v; asm volatile("ld.shared.u32 %0,[%1];\n" : "=r"(v) : "r"(a) : "memory"); return v;
}
__device__ __forceinline__ uint4 lds128(uint32_t a) {
    uint4 v; asm volatile("ld.shared.v4.u32 {%0,%1,%2,%3},[%4];\n" : "=r"(v.x), "=r"(v.y), "=r"(v.z), "=r"(v.w) : "r"(a) : "memory");
    return v;
}
__device__ __forceinline__ void sts32(uint32_t a, uint32_t v) { asm volatile("st.shared.u32 [%0],%1;\n" :: "r"(a), "r"(v) : "memory"); }
__device__ __forceinline__ void sts128(uint32_t a, uint32_t x, uint32_t y, uint32_t z, uint32_t w) {
    asm volatile("st.shared.v4.u32 [%0],{%1,%2,%3,%4};\n" :: "r"(a), "r"(x), "r"(y), "r"(z), "r"(w) : "memory");
}
__device__ __forceinline__ uint32_t pack_bf16(float lo, float hi) {
    uint32_t r; asm("cvt.rn.bf16x2.f32 %0,%1,%2;\n" : "=r"(r) : "f"(hi), "f"(lo)); return r;
}
__device__ __forceinline__ uint32_t pack_f16(float lo, float hi) {
    uint32_t r; asm("cvt.rn.f16x2.f32 %0,%1,%2;\n" : "=r"(r) : "f"(hi), "f"(lo)); return r;
}
__device__ __forceinline__ uint32_t badd2(uint32_t a, uint32_t b) {
    uint32_t r; asm("add.rn.bf16x2 %0,%1,%2;\n" : "=r"(r) : "r"(a), "r"(b)); return r;
}
__device__ __forceinline__ uint32_t bmul2(uint32_t a, uint32_t b) {
    uint32_t r; asm("mul.rn.bf16x2 %0,%1,%2;\n" : "=r"(r) : "r"(a), "r"(b)); return r;
}
__device__ __forceinline__ void sts64(uint32_t a, uint32_t x, uint32_t y) {
    asm volatile("st.shared.v2.u32 [%0],{%1,%2};\n" :: "r"(a), "r"(x), "r"(y) : "memory");
}
__device__ __forceinline__ uint2 lds64(uint32_t a) {
    uint2 v; asm volatile("ld.shared.v2.u32 {%0,%1},[%2];\n" : "=r"(v.x), "=r"(v.y) : "r"(a) : "memory"); return v;
}
__device__ __forceinline__ uint32_t bfma2(uint32_t a, uint32_t b, uint32_t c) {
    uint32_t r; asm("fma.rn.bf16x2 %0,%1,%2,%3;\n" : "=r"(r) : "r"(a), "r"(b), "r"(c)); return r;
}
__device__ __forceinline__ uint32_t plo(uint32_t a, uint32_t b) { return __byte_perm(a, b, 0x5410); }
__device__ __forceinline__ uint32_t phi(uint32_t a, uint32_t b) { return __byte_perm(a, b, 0x7632); }
__device__ __forceinline__ float bf_lo(uint32_t v) { return __uint_as_float(v << 16); }
__device__ __forceinline__ float bf_hi(uint32_t v) { return __uint_as_float(v & 0xFFFF0000u); }
__device__ __forceinline__ float bf_round(float x) { return __bfloat162float(__float2bfloat16_rn(x)); }

__device__ __forceinline__ void mbar_init(uint32_t a, uint32_t cnt) {
    asm volatile("mbarrier.init.shared.b64 [%0],%1;\n" :: "r"(a), "r"(cnt) : "memory");
}
__device__ __forceinline__ void mbar_arrive(uint32_t a) {
    asm volatile("mbarrier.arrive.shared.b64 _,[%0];\n" :: "r"(a) : "memory");
}
__device__ __forceinline__ void mbar_expect(uint32_t a, uint32_t bytes) {
    asm volatile("mbarrier.arrive.expect_tx.shared.b64 _,[%0],%1;\n" :: "r"(a), "r"(bytes) : "memory");
}
__device__ __forceinline__ void mbar_wait(uint32_t a) {
    uint32_t ok = 0;
#pragma unroll 1
    for (int it = 0; it < (1 << 20) && !ok; ++it)
        asm volatile("{.reg .pred p; mbarrier.try_wait.parity.shared.b64 p,[%1],0; selp.u32 %0,1,0,p;}\n"
                     : "=r"(ok) : "r"(a) : "memory");
}
__device__ __forceinline__ void mbar_wait_cluster(uint32_t a) {
    uint32_t ok = 0;
#pragma unroll 1
    for (int it = 0; it < (1 << 20) && !ok; ++it)
        asm volatile("{.reg .pred p; mbarrier.try_wait.parity.acquire.cluster.shared.b64 p,[%1],0; selp.u32 %0,1,0,p;}\n"
                     : "=r"(ok) : "r"(a) : "memory");
}

struct c32 { float x, y; };
__device__ __forceinline__ c32 csq(c32 z) { c32 r; r.x = fmaf(z.x, z.x, -(z.y * z.y)); r.y = (z.x + z.x) * z.y; return r; }
__device__ __forceinline__ c32 cexp_seed(float al2, float ai, float x) {
    float m, s, c, th = ai * x, e = al2 * x;
    asm("ex2.approx.ftz.f32 %0,%1;\n" : "=f"(m) : "f"(e));
    asm("sin.approx.ftz.f32 %0,%1;\n" : "=f"(s) : "f"(th));
    asm("cos.approx.ftz.f32 %0,%1;\n" : "=f"(c) : "f"(th));
    c32 r; r.x = m * c; r.y = m * s; return r;
}
typedef unsigned long long pc;
__device__ __forceinline__ pc mk64(uint32_t re, uint32_t im) { pc r; asm("mov.b64 %0,{%1,%2};\n" : "=l"(r) : "r"(re), "r"(im)); return r; }
__device__ __forceinline__ pc mkp(c32 a, c32 b) {
    pc r;
    asm("{.reg .b32 x,y; cvt.rn.f16x2.f32 x,%2,%1; cvt.rn.f16x2.f32 y,%4,%3; mov.b64 %0,{x,y};}\n"
        : "=l"(r) : "f"(a.x), "f"(b.x), "f"(a.y), "f"(b.y));
    return r;
}
__device__ __forceinline__ pc pmul(pc z, pc w) {
    pc r;
    asm("{.reg .b32 zr,zi,wr,wi,t0,t1,n; mov.b64 {zr,zi},%1; mov.b64 {wr,wi},%2;\n"
        "mul.rn.f16x2 t0,zr,wr; mul.rn.f16x2 t1,zi,wr; neg.f16x2 n,zi;\n"
        "fma.rn.f16x2 t0,n,wi,t0; fma.rn.f16x2 t1,zr,wi,t1; mov.b64 %0,{t0,t1};}\n"
        : "=l"(r) : "l"(z), "l"(w));
    return r;
}
__device__ __forceinline__ void stp(uint32_t a, pc v) {
    asm volatile("{.reg .b32 x,y; mov.b64 {x,y},%1; stmatrix.sync.aligned.m8n8.x2.shared.b16 [%0],{x,y};}\n"
                 :: "r"(a), "l"(v) : "memory");
}
__device__ __forceinline__ void mma_f16p(float (&d)[4], const uint32_t (&a)[4], pc b) {
    asm("{.reg .b32 x,y; mov.b64 {x,y},%8;\n"
        "mma.sync.aligned.m16n8k16.row.col.f32.f16.f16.f32 {%0,%1,%2,%3},{%4,%5,%6,%7},{x,y},{%0,%1,%2,%3};}\n"
        : "+f"(d[0]), "+f"(d[1]), "+f"(d[2]), "+f"(d[3]) : "r"(a[0]), "r"(a[1]), "r"(a[2]), "r"(a[3]), "l"(b));
}

__device__ __forceinline__ void store_pair(uint32_t a0, uint32_t a1, uint32_t v0, uint32_t v1, uint32_t v2, uint32_t v3,
                                           uint32_t v4, uint32_t v5, uint32_t v6, uint32_t v7) {
    sts128(a0, plo(v0, v1), plo(v2, v3), plo(v4, v5), plo(v6, v7));
    sts128(a1, phi(v0, v1), phi(v2, v3), phi(v4, v5), phi(v6, v7));
}

__device__ __forceinline__ void wgmma_n128(float (&d)[64], uint32_t a0, uint32_t a1, uint32_t a2, uint32_t a3, uint32_t dlo,
                                           int accumulate) {
    asm volatile("{.reg .pred p; .reg .b64 ds; setp.ne.s32 p,%69,0; mov.b64 ds,{%68,%70};\n"
                 "wgmma.mma_async.sync.aligned.m64n128k16.f32.bf16.bf16 {%0,%1,%2,%3,%4,%5,%6,%7,%8,%9,%10,%11,%12,%13,%14,%15,%16,%17,%18,%19,%20,%21,%22,%23,%24,%25,%26,%27,%28,%29,%30,%31,%32,%33,%34,%35,%36,%37,%38,%39,%40,%41,%42,%43,%44,%45,%46,%47,%48,%49,%50,%51,%52,%53,%54,%55,%56,%57,%58,%59,%60,%61,%62,%63},\n"
                 "{%64,%65,%66,%67},ds,p,1,1,0;}\n"
                 : "+f"(d[0]),"+f"(d[1]),"+f"(d[2]),"+f"(d[3]),"+f"(d[4]),"+f"(d[5]),"+f"(d[6]),"+f"(d[7]),"+f"(d[8]),"+f"(d[9]),"+f"(d[10]),"+f"(d[11]),"+f"(d[12]),"+f"(d[13]),"+f"(d[14]),"+f"(d[15]),"+f"(d[16]),"+f"(d[17]),"+f"(d[18]),"+f"(d[19]),"+f"(d[20]),"+f"(d[21]),"+f"(d[22]),"+f"(d[23]),"+f"(d[24]),"+f"(d[25]),"+f"(d[26]),"+f"(d[27]),"+f"(d[28]),"+f"(d[29]),"+f"(d[30]),"+f"(d[31]),"+f"(d[32]),"+f"(d[33]),"+f"(d[34]),"+f"(d[35]),"+f"(d[36]),"+f"(d[37]),"+f"(d[38]),"+f"(d[39]),"+f"(d[40]),"+f"(d[41]),"+f"(d[42]),"+f"(d[43]),"+f"(d[44]),"+f"(d[45]),"+f"(d[46]),"+f"(d[47]),"+f"(d[48]),"+f"(d[49]),"+f"(d[50]),"+f"(d[51]),"+f"(d[52]),"+f"(d[53]),"+f"(d[54]),"+f"(d[55]),"+f"(d[56]),"+f"(d[57]),"+f"(d[58]),"+f"(d[59]),"+f"(d[60]),"+f"(d[61]),"+f"(d[62]),"+f"(d[63])
                 : "r"(a0), "r"(a1), "r"(a2), "r"(a3), "r"(dlo), "r"(accumulate), "n"(128 >> 4));
}

template <int TS, int KMAX, int LO, int HI, int STRIDE>
__device__ __forceinline__ void toep_block(float (&acc)[4][2][4], const uint32_t (&kb)[KMAX + 1][2][2], uint32_t base,
                                           const uint32_t (&f0)[4], const uint32_t (&f1)[4]) {
    uint32_t fr[4][4];
#pragma unroll
    for (int j = 0; j < 4; ++j) { fr[0][j] = f0[j]; fr[1][j] = f1[j]; }
    if (LO + 2 <= HI) ldsm4t(fr[2], base + (uint32_t)((LO + 2) * STRIDE));
#pragma unroll
    for (int loc = LO; loc <= HI; ++loc) {
        if (loc + 3 <= HI) ldsm4t(fr[(loc + 3 - LO) & 3], base + (loc + 3) * STRIDE);
#pragma unroll
        for (int tj = 0; tj < 4; ++tj) {
            const int ks = TS * tj - loc;
            if (ks >= 0 && ks <= KMAX) {
                mma_bf16(acc[tj][0], fr[(loc - LO) & 3], kb[ks][0][0], kb[ks][0][1]);
                mma_bf16(acc[tj][1], fr[(loc - LO) & 3], kb[ks][1][0], kb[ks][1][1]);
            }
        }
    }
}

__device__ __forceinline__ uint32_t gate_word(float s) {
    float sb = bf_round(s);
    float g = bf_round(1.0f / (1.0f + expf(-sb)));
    float o = bf_round(1.0f - g);
    return ((__float_as_uint(g) >> 16) | (__float_as_uint(o) & 0xFFFF0000u)) & 0x7FFF7FFFu;
}

__device__ __forceinline__ void final_block(const CUtensorMap* tm, uint32_t sb, int cl, int rank, int un, int b, int barid) {
    uint32_t oaddr, obar;
    asm("mapa.shared::cluster.u32 %0,%1,%2;\n" : "=r"(oaddr) : "r"(sb + OFF_OUT + b * 2048 + un * 16), "r"(rank ^ 1));
    asm("mapa.shared::cluster.u32 %0,%1,%2;\n" : "=r"(obar) : "r"(sb + OFF_MB_OUT + 8 * b), "r"(rank ^ 1));
    const uint32_t orow = sb + OFF_ROWS + b * 4096 + (un >> 6) * 2048 + (un & 63) * 16;
    const uint32_t sw = ((2 * un) ^ ((un >> 1) & 0x18)) * 4 + b * 1024;
    const uint32_t psel = rank ? 0x7632u : 0x5410u;
    uint2 ya[4], yb[4];
    const uint4 gw = lds128(sb + OFF_GT + (b * 256 + 2 * un) * 8);
#pragma unroll
    for (int c = 0; c < 4; ++c) {
        ya[c] = lds64(sb + OFF_S1P + c * 8192 + sw);
        yb[c] = lds64(sb + OFF_S1P + c * 8192 + 4096 + sw);
    }
    if (b > 0) {
        mbar_wait(sb + OFF_MB_P + 8 * b);
#pragma unroll
        for (int c = 0; c < 4; ++c) {
            const uint2 za = lds64(sb + OFF_PG2 - 1024 + c * 6144 + sw);
            const uint2 zb = lds64(sb + OFF_PG2 - 1024 + c * 6144 + 3072 + sw);
            ya[c].x = badd2(ya[c].x, za.x); ya[c].y = badd2(ya[c].y, za.y);
            yb[c].x = badd2(yb[c].x, zb.x); yb[c].y = badd2(yb[c].y, zb.y);
        }
    }
    uint32_t o0[4], o1[4];
#pragma unroll
    for (int c = 0; c < 4; ++c) {
        o0[c] = bfma2(ya[c].x, gw.x, bmul2(yb[c].x, gw.y));
        o1[c] = bfma2(ya[c].y, gw.z, bmul2(yb[c].y, gw.w));
    }
    asm volatile("st.async.weak.shared::cluster.mbarrier::complete_tx::bytes.v4.b32 [%0],{%1,%2,%3,%4},[%5];\n"
                 :: "r"(oaddr), "r"(__byte_perm(o0[0], o0[1], psel ^ 0x2222u)), "r"(__byte_perm(o0[2], o0[3], psel ^ 0x2222u)),
                    "r"(__byte_perm(o1[0], o1[1], psel ^ 0x2222u)), "r"(__byte_perm(o1[2], o1[3], psel ^ 0x2222u)),
                    "r"(obar) : "memory");
    sts64(orow + rank * 8, __byte_perm(o0[0], o0[1], psel), __byte_perm(o0[2], o0[3], psel));
    sts64(orow + 1024 + rank * 8, __byte_perm(o1[0], o1[1], psel), __byte_perm(o1[2], o1[3], psel));
    mbar_wait_cluster(sb + OFF_MB_OUT + 8 * b);
    const uint4 pe = lds128(sb + OFF_OUT + b * 2048 + un * 16);
    sts64(orow + 8 - rank * 8, pe.x, pe.y);
    sts64(orow + 1032 - rank * 8, pe.z, pe.w);
    asm volatile("fence.proxy.async.shared::cta;\n" ::: "memory");
    asm volatile("bar.sync %0, 128;\n" :: "r"(barid) : "memory");
    if (un == 0) {
        asm volatile("cp.async.bulk.tensor.4d.global.shared::cta.bulk_group [%0,{%1,%2,%3,%4}],[%5];\n"
                     :: "l"(tm), "r"(8 * cl), "r"(64 * rank), "r"(0), "r"(2 * b), "r"(sb + OFF_ROWS + b * 4096) : "memory");
        asm volatile("cp.async.bulk.commit_group;\n" ::: "memory");
    }
}

__global__ void __cluster_dims__(2, 1, 1) __launch_bounds__(NTHREADS, 1)
fused_s4d_kernel(const __grid_constant__ Params prm, const __grid_constant__ CUtensorMap tm_in,
                 const __grid_constant__ CUtensorMap tm_out) {
    extern __shared__ __align__(1024) unsigned char smem[];
    const uint32_t sb = (uint32_t)__cvta_generic_to_shared(smem);
    const int tid = threadIdx.x, warp = tid >> 5, lane = tid & 31;
    const int rank = blockIdx.x & 1, cl = blockIdx.x >> 1;
    if (warp != 8) asm volatile("barrier.cluster.arrive.relaxed.aligned;\n" ::: "memory");
    STAMP(0);
    if (tid == 128) GSTAMP(0);

    if (warp >= 8) {
        const int un = tid - 256;
        if (warp == 8) {
            if (lane == 0) {
                asm volatile("prefetch.tensormap [%0];\n" :: "l"(&tm_in) : "memory");
                asm volatile("prefetch.tensormap [%0];\n" :: "l"(&tm_out) : "memory");
                mbar_init(sb + OFF_MB_U, 1);
                mbar_init(sb + OFF_MB_P, 16);
#pragma unroll
                for (int i = 1; i < 4; ++i) mbar_init(sb + OFF_MB_P + 8 * i, 4);
#pragma unroll
                for (int i = 0; i < 4; ++i) mbar_init(sb + OFF_MB_OUT + 8 * i, 1);
                mbar_expect(sb + OFF_MB_U, 32768);
#pragma unroll
                for (int i = 0; i < 4; ++i) mbar_expect(sb + OFF_MB_OUT + 8 * i, 2048);
                asm volatile("fence.mbarrier_init.release.cluster;\n" ::: "memory");
                asm volatile("fence.proxy.async.shared::cta;\n" ::: "memory");
            }
            __syncwarp();
            asm volatile("barrier.cluster.arrive.relaxed.aligned;\n" ::: "memory");
        }
        asm volatile("barrier.cluster.wait.acquire.aligned;\n" ::: "memory");
        if (un == 0) {
            asm volatile("cp.async.bulk.tensor.3d.shared::cluster.global.mbarrier::complete_tx::bytes.multicast::cluster "
                         "[%0],[%1,{%2,%3,%4}],[%5],%6;\n"
                         :: "r"(sb + OFF_U + rank * 16384), "l"(&tm_in), "r"(8 * cl), "r"(0), "r"(8 * rank), "r"(sb + OFF_MB_U),
                            "h"((uint16_t)3) : "memory");
        }
        STAMP(9);
        {
            const uint32_t a2 = sb + OFF_SG2 + (warp - 8) * SG2_CH;
            sts128(a2 + (lane < 16 ? G2_W5 : G2_W3) + ((lane & 15) + ((lane >> 3) & 1)) * 16, 0, 0, 0, 0);
            if (lane < 16) sts128(a2 + (lane < 4 ? G2_W9E : lane < 8 ? G2_W9O : lane < 12 ? G2_W7E : G2_W7O) + (lane & 3) * 16, 0, 0, 0, 0);
            sts128(sb + OFF_V + (warp - 8) * V_CH + (lane >> 4) * V_H + (lane & 15) * 16, 0, 0, 0, 0);
        }
        const int g = lane >> 2, q = lane & 3;
        uint32_t epoch = 0;
        if (warp == 8) asm volatile("ld.relaxed.gpu.global.u32 %0,[%1];\n" : "=r"(epoch) : "l"(&g_epoch) : "memory");
        uint4 gx[8], gwv[4];
        const uint4* ur = reinterpret_cast<const uint4*>(prm.u) + (size_t)(blockIdx.x * 16 + g) * 64 + (warp - 8) * 16 + q;
        const uint4* wr = reinterpret_cast<const uint4*>(prm.gw) + (warp - 8) * 16 + q;
#pragma unroll
        for (int j = 0; j < 4; ++j) { gx[2 * j] = __ldg(ur + 4 * j); gx[2 * j + 1] = __ldg(ur + 8 * 64 + 4 * j); gwv[j] = __ldg(wr + 4 * j); }
        {
            float gs[4] = {0.f, 0.f, 0.f, 0.f}, gt[4] = {0.f, 0.f, 0.f, 0.f};
#pragma unroll
            for (int j = 0; j < 4; ++j) {
                uint32_t a[4], b[4];
                a[0] = bmul2(gx[2 * j].x, gwv[j].x); a[1] = bmul2(gx[2 * j + 1].x, gwv[j].x);
                a[2] = bmul2(gx[2 * j].y, gwv[j].y); a[3] = bmul2(gx[2 * j + 1].y, gwv[j].y);
                b[0] = bmul2(gx[2 * j].z, gwv[j].z); b[1] = bmul2(gx[2 * j + 1].z, gwv[j].z);
                b[2] = bmul2(gx[2 * j].w, gwv[j].w); b[3] = bmul2(gx[2 * j + 1].w, gwv[j].w);
                mma_bf16(gs, a, 0x3F803F80u, 0x3F803F80u);
                mma_bf16(gt, b, 0x3F803F80u, 0x3F803F80u);
            }
            if (q == 0) {
                sts32(sb + OFF_GPART + ((warp - 8) * 16 + g) * 4, __float_as_uint(gs[0] + gt[0]));
                sts32(sb + OFF_GPART + ((warp - 8) * 16 + g + 8) * 4, __float_as_uint(gs[2] + gt[2]));
            }
            asm volatile("bar.sync 1, 128;\n" ::: "memory");
            if (warp == 8) {
                const uint32_t tg = (epoch + 1u) & 3u;
                if (lane < 16) {
                    float t = 0.f;
#pragma unroll
                    for (int w = 0; w < 4; ++w) t += __uint_as_float(lds32(sb + OFF_GPART + (w * 16 + lane) * 4));
                    const uint32_t wd = gate_word(t) | ((tg & 1u) << 15) | ((tg & 2u) << 30);
                    asm volatile("st.relaxed.gpu.global.u32 [%0],%1;\n" :: "l"(&g_gate[blockIdx.x * 16 + lane]), "r"(wd) : "memory");
                }
                if (lane == 0) {
                    sts32(sb + OFF_TAG, ((tg & 1u) << 15) | ((tg & 2u) << 30));
                    sts32(sb + OFF_TAG + 4, epoch + 1u);
                }
            }
        }
        STAMP(10);
        mbar_wait(sb + OFF_MB_U);
        STAMP(2);
        {
            const uint32_t ua = sb + OFF_U + un * 16 + rank * 8;
            uint2 v[16];
#pragma unroll
            for (int j = 0; j < 16; ++j) v[j] = lds64(ua + j * 2048);
            const uint32_t a = sb + OFF_V + (16 + un) * 16;
            store_pair(a, a + V_CH, v[0].x, v[1].x, v[2].x, v[3].x, v[4].x, v[5].x, v[6].x, v[7].x);
            store_pair(a + V_H, a + V_H + V_CH, v[8].x, v[9].x, v[10].x, v[11].x, v[12].x, v[13].x, v[14].x, v[15].x);
            store_pair(a + 2 * V_CH, a + 3 * V_CH, v[0].y, v[1].y, v[2].y, v[3].y, v[4].y, v[5].y, v[6].y, v[7].y);
            store_pair(a + V_H + 2 * V_CH, a + V_H + 3 * V_CH, v[8].y, v[9].y, v[10].y, v[11].y, v[12].y, v[13].y, v[14].y, v[15].y);
        }
        asm volatile("fence.proxy.async.shared::cta;\n" ::: "memory");
        asm volatile("bar.arrive 2, 384;\n" ::: "memory");
        STAMP(3);
        asm volatile("bar.sync 9, 384;\n" ::: "memory");
#pragma unroll 1
        for (int it = 0; it < 3; ++it) {
            if (it == 2) {
                asm volatile("bar.arrive 3, 256;\n" ::: "memory");
                STAMP(4);
            }
            const int rho = it * 32 + lane;
            const uint32_t va = sb + OFF_V + (warp - 8) * V_CH + (16 + rho) * 16;
            const uint4 e0 = lds128(va + V_H - 16), e1 = lds128(va), e2 = lds128(va + V_H), e3 = lds128(va + 16);
            const uint32_t E[13] = {e0.z, e0.w, e1.x, e1.y, e1.z, e1.w, e2.x, e2.y, e2.z, e2.w, e3.x, e3.y, e3.z};
            uint32_t O[12], P2[12], W3[12], P4[11], W5[11];
#pragma unroll
            for (int k = 0; k < 12; ++k) { O[k] = __byte_perm(E[k], E[k + 1], 0x5432); P2[k] = badd2(E[k], O[k]); }
#pragma unroll
            for (int k = 1; k < 12; ++k) W3[k] = badd2(O[k - 1], P2[k]);
#pragma unroll
            for (int k = 0; k < 11; ++k) P4[k] = badd2(P2[k], P2[k + 1]);
#pragma unroll
            for (int k = 2; k < 11; ++k) W5[k] = badd2(P4[k - 1], E[k + 1]);
            const uint32_t s2a = sb + OFF_SG2 + (warp - 8) * SG2_CH;
            const int c5 = 2 * rho + 16;
            const uint32_t a5 = s2a + G2_W5 + (c5 + (c5 >> 3)) * 16, a3 = a5 + (G2_W3 - G2_W5);
            sts128(a5, W5[2], W5[3], W5[4], W5[5]); sts128(a5 + 16, W5[6], W5[7], W5[8], W5[9]);
            sts128(a3, W3[4], W3[5], W3[6], W3[7]); sts128(a3 + 16, W3[8], W3[9], W3[10], W3[11]);
            if (it < 2) {
                uint32_t W7[8], W9[8];
#pragma unroll
                for (int k = 0; k < 8; ++k) { W7[k] = badd2(W3[k + 1], P4[k + 2]); W9[k] = badd2(P4[k], W5[k + 3]); }
                const uint32_t a9 = s2a + (rho + 4) * 16, ap = s2a + rho * 16;
                sts128(a9 + G2_W9E, W9[0], W9[1], W9[2], W9[3]); sts128(a9 + G2_W9O, W9[4], W9[5], W9[6], W9[7]);
                sts128(a9 + G2_W7E, W7[0], W7[1], W7[2], W7[3]); sts128(a9 + G2_W7O, W7[4], W7[5], W7[6], W7[7]);
                sts128(ap + G2_P2E, P2[0], P2[1], P2[2], P2[3]); sts128(ap + G2_P2O, P2[4], P2[5], P2[6], P2[7]);
                if (rho == 0) {
                    const uint32_t n12 = plo(E[2], P2[2]);
                    sts128(a5 - 32, 0, 0, 0, n12);
                    sts128(a3 - 32, 0, W3[1], W3[2], W3[3]);
                    sts128(a9 + G2_W9O - 16, 0, 0, n12, __byte_perm(W3[2], P4[2], 0x5432));
                    sts128(a9 + G2_W7O - 16, 0, 0, E[2] << 16, __byte_perm(P2[2], W3[2], 0x7610));
                }
            }
        }
        asm volatile("bar.arrive 4, 256;\n" ::: "memory");
        {
            const int uc = un;
            const uint32_t tagw = lds32(sb + OFF_TAG);
            bool done = false;
            const int tb0 = (uc >> 5) * 256 + (uc & 31) * 4;
#pragma unroll 1
            for (int tries = 0; tries < 8192 && !done; ++tries) {
                uint4 v[4];
#pragma unroll
                for (int i = 0; i < 4; ++i)
                    asm volatile("ld.relaxed.gpu.global.v4.u32 {%0,%1,%2,%3},[%4];\n"
                                 : "=r"(v[i].x), "=r"(v[i].y), "=r"(v[i].z), "=r"(v[i].w)
                                 : "l"(&g_gate[tb0 + (i >> 1) * 1024 + (i & 1) * 128]) : "memory");
                uint32_t bad = 0;
#pragma unroll
                for (int i = 0; i < 4; ++i)
                    bad |= (v[i].x ^ tagw) | (v[i].y ^ tagw) | (v[i].z ^ tagw) | (v[i].w ^ tagw);
                done = __all_sync(0xffffffffu, (bad & 0x80008000u) == 0);
                if (done) {
#pragma unroll
                    for (int i = 0; i < 2; ++i) {
                        const uint4 a = v[2 * i], b = v[2 * i + 1];
                        const uint32_t d = sb + OFF_GT + (i * 512 + uc * 4) * 8;
                        sts128(d, plo(a.x, b.x) & 0x7FFF7FFFu, phi(a.x, b.x) & 0x7FFF7FFFu, plo(a.y, b.y) & 0x7FFF7FFFu, phi(a.y, b.y) & 0x7FFF7FFFu);
                        sts128(d + 16, plo(a.z, b.z) & 0x7FFF7FFFu, phi(a.z, b.z) & 0x7FFF7FFFu, plo(a.w, b.w) & 0x7FFF7FFFu, phi(a.w, b.w) & 0x7FFF7FFFu);
                    }
                } else {
                    __nanosleep(64);
                }
            }
            if (!done) {
#pragma unroll 1
                for (int k = 0; k < 512; ++k) {
                    const int t = (k >> 8) * 1024 + (uc >> 5) * 256 + (k & 255);
                    float s = 0.f;
#pragma unroll 1
                    for (int j = 0; j < 8; ++j) {
                        const uint32_t pr = bmul2(reinterpret_cast<const uint32_t*>(prm.u)[t * 256 + j * 32 + lane],
                                                  reinterpret_cast<const uint32_t*>(prm.gw)[j * 32 + lane]);
                        s += bf_lo(pr) + bf_hi(pr);
                    }
#pragma unroll
                    for (int o = 16; o > 0; o >>= 1) s += __shfl_xor_sync(0xffffffffu, s, o);
                    if (lane == 0) {
                        const uint32_t wd = gate_word(s);
                        const uint32_t d = sb + OFF_GT + ((t >> 8) * 128 + (t & 127)) * 8 + ((t >> 7) & 1) * 2;
                        asm volatile("st.shared.u16 [%0],%1;\n" :: "r"(d), "h"((uint16_t)(wd & 0xFFFFu)) : "memory");
                        asm volatile("st.shared.u16 [%0],%1;\n" :: "r"(d + 4), "h"((uint16_t)(wd >> 16)) : "memory");
                    }
                }
            }
        }
        asm volatile("bar.sync 1, 128;\n" ::: "memory");
        STAMP(11);
        if (un == 32) {
            asm volatile("{.reg .pred p; .reg .u32 n;\n"
                         "atom.relaxed.gpu.global.inc.u32 n,[%0],%2;\n"
                         "setp.eq.u32 p,n,%2;\n"
                         "@p st.relaxed.gpu.global.u32 [%1],%3;}\n"
                         :: "l"(&g_arrived), "l"(&g_epoch), "r"(gridDim.x - 1), "r"(lds32(sb + OFF_TAG + 4)) : "memory");
        }
        __syncwarp();
        asm volatile("bar.arrive 10, 256;\n" ::: "memory");
        mbar_wait(sb + OFF_MB_P);
#pragma unroll 1
        for (int b = 0; b < 4; b += (b == 1) ? 2 : 1) {
            final_block(&tm_out, sb, cl, rank, un, b, 1);
            STAMP(5 + b);
        }
        if (un == 0) {
            asm volatile("cp.async.bulk.wait_group.read 0;\n" ::: "memory");
            STAMP(13);
            GSTAMP(1);
        }
        return;
    }

    const int ch = warp & 3, role = warp >> 2;
    const int chg = 8 * cl + 4 * rank + ch;
    const int g = lane >> 2, q = lane & 3;

    uint2 pLA, pAI, pCR, pCI;
    {
        const size_t o = (size_t)chg * 128 + lane * 4;
        pLA = __ldg(reinterpret_cast<const uint2*>(prm.p[role][0] + o));
        pAI = __ldg(reinterpret_cast<const uint2*>(prm.p[role][1] + o));
        pCR = __ldg(reinterpret_cast<const uint2*>(prm.p[role][2] + o));
        pCI = __ldg(reinterpret_cast<const uint2*>(prm.p[role][3] + o));
    }
    const float log_dt = __bfloat162float(prm.p[role][4][chg]);
    const float dskip = __bfloat162float(prm.p[role][5][chg]);

    const uint32_t kt = sb + OFF_KT + warp * KT_W;
    {
        if (lane < 30) sts64(kt + KT_WD1 + (lane < 14 ? lane : 258 + lane) * 8, 0u, 0u);
        const uint32_t z2 = kt + KT_WD4 + (lane < 7 ? lane : 64 + lane) * 4;
        if (lane < 16) { sts32(z2, 0u); sts32(z2 + 320, 0u); }
    }
    float dt = 0.f, fscale = 0.f, cinv = 0.f, f0 = 0.f;
    float dk[5][4];
#pragma unroll
    for (int j = 0; j < 5; ++j) { dk[j][0] = dk[j][1] = dk[j][2] = dk[j][3] = 0.f; }
    {
        const uint32_t tb = sb + OFF_FT + warp * FT_W;
        const int mat = lane >> 3, rr = lane & 7;
        const uint32_t stb = tb + (71 * rr + 8 * (mat & 1)) * 16, stc = tb + (71 * rr + 64 + (mat & 1)) * 16;
        const uint32_t ld0 = tb + ((mat & 1) ? 64 + (mat >> 1) : 8 * (mat >> 1) + rr) * 16;
        const uint32_t ld1 = tb + (16 + 8 * mat + rr) * 16;
        const uint32_t ld2 = tb + ((mat & 2) ? 64 + mat : 48 + 8 * mat + rr) * 16;
        const uint32_t ld3 = tb + (71 * (mat >> 1) + 68 + (mat & 1)) * 16;
#pragma unroll
        for (int r = 0; r < 2; ++r) {
            uint32_t wLA = 0u, wAI = 0u, wCR = 0u, wCI = 0u;
            if (r == 0) {
                dt = bf_round(expf(log_dt));
                uint32_t m = max(max(max(pCR.x & 0x7F80u, (pCR.x >> 16) & 0x7F80u), max(pCR.y & 0x7F80u, (pCR.y >> 16) & 0x7F80u)),
                                 max(max(pCI.x & 0x7F80u, (pCI.x >> 16) & 0x7F80u), max(pCI.y & 0x7F80u, (pCI.y >> 16) & 0x7F80u)));
                m = __reduce_max_sync(0xffffffffu, m) >> 7;
                m = min(max(m, 1u), 253u);
                cinv = __uint_as_float((254u - m) << 23);
                fscale = 2.0f * dt * __uint_as_float(m << 23);
                wLA = pLA.x; wAI = pAI.x; wCR = pCR.x; wCI = pCI.x;
                STAMP(1);
            } else if (r == 1) {
                f0 = (bf_lo(pCR.x) + bf_hi(pCR.x)) + (bf_lo(pCR.y) + bf_hi(pCR.y));
#pragma unroll
                for (int o = 16; o > 0; o >>= 1) f0 += __shfl_xor_sync(0xffffffffu, f0, o);
                f0 = fmaf(2.0f * dt, f0, dskip);
                wLA = pLA.y; wAI = pAI.y; wCR = pCR.y; wCI = pCI.y;
            }
            float ea, eb;
            asm("ex2.approx.ftz.f32 %0,%1;\n" : "=f"(ea) : "f"(bf_lo(wLA) * 1.4426950408889634f));
            asm("ex2.approx.ftz.f32 %0,%1;\n" : "=f"(eb) : "f"(bf_hi(wLA) * 1.4426950408889634f));
            const uint32_t e2 = pack_bf16(ea, eb);
            const float ala = (-bf_lo(e2) * dt) * 1.4426950408889634f, alb = (-bf_hi(e2) * dt) * 1.4426950408889634f;
            const float aia = bf_lo(wAI) * dt, aib = bf_hi(wAI) * dt;
            const pc C = mk64(pack_f16(bf_lo(wCR) * cinv, bf_hi(wCR) * cinv), pack_f16(bf_lo(wCI) * cinv, bf_hi(wCI) * cinv));
            {
                c32 a = cexp_seed(ala, -aia, 16.f), b = cexp_seed(alb, -aib, 16.f);
                const pc f1 = mkp(a, b); a = csq(a); b = csq(b);
                const pc f2 = mkp(a, b); a = csq(a); b = csq(b);
                const pc f4 = mkp(a, b); a = csq(a); b = csq(b);
                stp(stb, 0x3C003C00ull);
                stp(stb + 16, f1); stp(stb + 32, f2); stp(stb + 64, f4); stp(stc, mkp(a, b));
                c32 a256 = csq(a), b256 = csq(b);
                a256.y = -a256.y; b256.y = -b256.y;
                const pc f3 = pmul(f1, f2);
                stp(stb + 48, f3); stp(stb + 80, pmul(f1, f4)); stp(stb + 96, pmul(f2, f4)); stp(stb + 112, pmul(f3, f4));
                a = cexp_seed(ala, aia, 1.f); b = cexp_seed(alb, aib, 1.f);
                const pc w1 = mkp(a, b); a = csq(a); b = csq(b);
                const pc w2 = mkp(a, b); a = csq(a); b = csq(b);
                const pc w4 = mkp(a, b); a = csq(a); b = csq(b);
                const pc w8 = mkp(a, b);
                stp(stc + 32, w1);
                pc D[4];
                D[0] = pmul(C, w1); D[1] = pmul(D[0], w2); D[2] = pmul(D[0], w4); D[3] = pmul(D[1], w4);
#pragma unroll
                for (int j = 0; j < 4; ++j) { stp(stb + 256 + 16 * j, D[j]); stp(stb + 320 + 16 * j, pmul(D[j], w8)); }
                a = a256; b = b256;
                const pc w256 = mkp(a, b); a = csq(a); b = csq(b);
                const pc w512 = mkp(a, b); a = csq(a); b = csq(b);
                const pc w1024 = mkp(a, b);
                stp(stc + 64, w256);
                D[0] = pmul(C, w4); D[1] = pmul(C, w8); D[2] = pmul(D[0], w8); D[3] = pmul(D[1], w8);
#pragma unroll
                for (int j = 0; j < 4; ++j) {
                    const pc t = pmul(D[j], w512);
                    stp(stb + 512 + 16 * j, t); stp(stb + 576 + 16 * j, pmul(t, w256));
                }
#pragma unroll
                for (int j = 0; j < 2; ++j) {
                    const pc t = pmul(D[2 * j + 1], w1024), t2 = pmul(t, w256);
                    stp(stb + 768 + 16 * j, t); stp(stb + 800 + 16 * j, t2);
                    stp(stb + 832 + 16 * j, pmul(t, w512)); stp(stb + 864 + 16 * j, pmul(t2, w512));
                }
            }
            __syncwarp();
#pragma unroll
            for (int s = 0; s < 8; s += 2) {
                uint32_t W[4];
                ldsm4(W, ld3 + s * 1136);
#pragma unroll
                for (int h = 0; h < 2; ++h) {
                    uint32_t L0[4], L1[4], L2[4];
                    ldsm4(L0, ld0 + (s + h) * 1136); ldsm4(L1, ld1 + (s + h) * 1136); ldsm4(L2, ld2 + (s + h) * 1136);
                    uint32_t A[4];
                    A[0] = L0[0]; A[2] = L0[2];
                    asm("{.reg .b32 t0,t1,n; mul.rn.f16x2 t0,%2,%4; mul.rn.f16x2 t1,%3,%4; neg.f16x2 n,%3;\n"
                        "fma.rn.f16x2 %0,n,%5,t0; fma.rn.f16x2 %1,%2,%5,t1;}\n"
                        : "=r"(A[1]), "=r"(A[3]) : "r"(L0[0]), "r"(L0[2]), "r"(L0[1]), "r"(L0[3]));
                    const pc t1 = pmul(mk64(L1[0], L1[1]), mk64(L2[2], L2[3]));
                    const pc t2 = pmul(t1, mk64(W[2 * h], W[2 * h + 1]));
                    mma_f16(dk[0], A, L1[0], L1[1]);
                    mma_f16(dk[3], A, L1[2], L1[3]);
                    mma_f16(dk[4], A, L2[0], L2[1]);
                    mma_f16p(dk[1], A, t1);
                    mma_f16p(dk[2], A, t2);
                }
            }
            __syncwarp();
        }
    }
    STAMP(2);

    {
        const bool last = (lane == 31);
#pragma unroll
        for (int j = 0; j < 5; ++j)
#pragma unroll
            for (int c = 0; c < 4; ++c) dk[j][c] *= fscale;
        const float f256 = dk[1][3], f512 = dk[2][3], f1024 = dk[3][3];
        if (last) { dk[2][2] -= f512; dk[2][3] = 0.f; }
        const float n0 = __shfl_sync(0xffffffffu, dk[0][0], (lane + 1) & 31), n1 = __shfl_sync(0xffffffffu, dk[0][2], (lane + 1) & 31);
        const float p0 = __shfl_sync(0xffffffffu, lane == 31 ? f256 : dk[2][1], (lane + 31) & 31);
        const float p1 = __shfl_sync(0xffffffffu, lane == 31 ? dk[2][1] : dk[2][3], (lane + 31) & 31);
#pragma unroll
        for (int hh = 0; hh < 2; ++hh) {
            const float a = dk[0][2 * hh], b = dk[1][2 * hh], c = dk[0][2 * hh + 1], d = dk[1][2 * hh + 1];
            const float an = hh == 0 ? (last ? n1 : n0) : (last ? d : n1);
            const uint32_t wa = kt + KT_WD1 + (16 + 4 * lane + 128 * hh) * 8;
            const float be = dk[2][2 * hh], al = dk[2][2 * hh + 1];
            const uint32_t aa = pack_bf16(al, al);
            const uint32_t w0 = pack_bf16(b, a), w1 = pack_bf16(c, b), w2 = pack_bf16(d, c), w3 = pack_bf16(an, d);
            sts128(wa, w0, pack_bf16(be, hh == 0 ? p0 : p1), w1, pack_bf16(al, be));
            sts128(wa + 16, w2, aa, w3, aa);
            if (hh == 1 && lane >= 28) {
                sts32(wa - 2048 + 4, w0); sts32(wa - 2048 + 12, w1); sts32(wa - 2048 + 20, w2); sts32(wa - 2048 + 28, w3);
            }
        }
        if (lane == 0) { sts32(kt + KT_WD1 + 14 * 8, pack_bf16(f0, 0.f)); sts32(kt + KT_WD1 + 15 * 8, pack_bf16(dk[0][0], f0)); }
#pragma unroll
        for (int hh = 0; hh < 2; ++hh) {
            const int i = g + 8 * hh;
            sts32(kt + KT_WD4 + (2 * i + (q & 1) + 32 * (q >> 1) + 8) * 4, pack_bf16(dk[3][2 * hh + 1], dk[3][2 * hh]));
            sts32(kt + KT_WD4 + 320 + (i + 16 * q + 7) * 4, pack_bf16(dk[4][2 * hh + 1], dk[4][2 * hh]));
        }
        if (last) {
            const uint32_t w512 = pack_bf16(f512, 0.f);
            sts32(kt + KT_WD4 + 7 * 4, w512);
            sts128(kt + KT_WD1 + 274 * 8, w512, 0u, w512, 0u);
            sts32(kt + KT_FIX, pack_bf16(f1024, f1024));
        }
    }
    STAMP(3);
    asm volatile("bar.sync 2, 384;\n" ::: "memory");
    STAMP(6);

    const uint32_t ktA = sb + OFF_KT + ch * KT_W, ktB = ktA + 4 * KT_W;
    const int mat = lane >> 3, rr = lane & 7;
    const int np = 4 * (g & 1) + (g >> 1);
    uint32_t k4[9][2][2], k8[8][2][2], kf[2];
    const uint32_t o4 = KT_WD4 + (g - q + 7) * 4;
    const uint32_t o8 = KT_WD4 + 320 + (np + 7 - q) * 4;
#define K_LOAD(DST, OFF, KS)                                                                                 \
        { DST[KS][0][0] = lds32(ktA + OFF + (8 * (KS)) * 4); DST[KS][0][1] = lds32(ktA + OFF + (8 * (KS) - 4) * 4); \
          DST[KS][1][0] = lds32(ktB + OFF + (8 * (KS)) * 4); DST[KS][1][1] = lds32(ktB + OFF + (8 * (KS) - 4) * 4); }
    {
        const int rb = ch >> 1, br = ch & 1;
        const int urole = __shfl_sync(0xffffffffu, role, 0);
        uint32_t wa = sb + OFF_KT + (br * 4 + role) * KT_W + KT_WD1 + (14 + 8 * rb + g - 2 * q) * 8;
        uint2 af[17][2];
#define A_LOAD(S)                                                                                            \
        if ((S) < 16) { af[S][0] = lds64(wa + 128 * (S)); af[S][1] = lds64(wa + 128 * (S) - 64); }           \
        else { af[S][0] = make_uint2(0u, lds32(wa + 128 * (S) + 4)); af[S][1] = make_uint2(0u, lds32(wa + 128 * (S) - 60)); }
        if (urole) asm volatile("bar.sync 9, 384;\n" ::: "memory");
#pragma unroll
        for (int s = 0; s < 9; ++s) { A_LOAD(s) }
#pragma unroll 1
        for (int cc = 0; cc < 2; ++cc) {
#pragma unroll
            for (int s = 9; s < 17; ++s) { A_LOAD(s) }
            const int c = urole + 2 * cc;
            const uint32_t desc = (((sb + OFF_V + c * V_CH + 256) & 0x3FFFFu) >> 4) | ((V_H >> 4) << 16);
            float d[64];
            if (urole | cc) asm volatile("bar.sync %0, 256;\n" :: "r"(5 + urole) : "memory");
            else asm volatile("bar.arrive 9, 384;\n" ::: "memory");
            asm volatile("wgmma.fence.sync.aligned;\n" ::: "memory");
#pragma unroll
            for (int s = 0; s < 9; ++s) wgmma_n128(d, af[s][0].x, af[s][0].y, af[s][1].x, af[s][1].y, desc - s, s);
            asm volatile("wgmma.commit_group.sync.aligned;\n" ::: "memory");
#pragma unroll
            for (int s = 9; s < 17; ++s)
                wgmma_n128(d, af[s][0].x, af[s][0].y, af[s][1].x, af[s][1].y, desc - s, 1);
            asm volatile("wgmma.commit_group.sync.aligned;\n" ::: "memory");
            if (!(urole & cc)) asm volatile("bar.arrive %0, 256;\n" :: "r"(6 - urole) : "memory");
            asm volatile("wgmma.wait_group.sync.aligned 1;\n" ::: "memory");
            wa += 2 * KT_W;
            if (cc == 0) {
#pragma unroll
                for (int s = 0; s < 9; ++s) { A_LOAD(s) }
            }
            asm volatile("wgmma.wait_group.sync.aligned 0;\n" ::: "memory");
#pragma unroll
            for (int i = 0; i < 64; ++i) asm volatile("" : "+f"(d[i]) :: "memory");
            if (urole & cc) asm volatile("bar.arrive 7, 256;\n" ::: "memory");
            if (cc == 0) STAMP(4); else STAMP(5);
            if (rb == 1 && (lane | 4) == 31) {
                const uint32_t u01 = lds32(sb + OFF_V + c * V_CH + 256);
                const float f512 = bf_lo(lds32(wa - 2 * KT_W + 252 * 8));
                d[13] = fmaf(f512, lane == 27 ? bf_lo(u01) : bf_lo(u01) + bf_hi(u01), d[13]);
            }
            const uint32_t dst = sb + OFF_S1P + c * 8192 + br * 4096 + (32 * q + g) * 4;
#pragma unroll
            for (int j = 0; j < 16; j += 2)
#pragma unroll
                for (int e = 0; e < 2; ++e) {
                    const float y0 = j >= 2 ? d[4 * j + e] + d[4 * j - 6 + e] : d[4 * j + e];
                    const float y1 = j >= 2 ? d[4 * j + 4 + e] + d[4 * j - 2 + e] : d[4 * j + 4 + e];
                    sts32(dst + j * 256 + ((16 * e + 8 * rb) ^ (8 * q)) * 4, pack_bf16(y0, y1));
                }
            __syncwarp();
            if (lane == 0) mbar_arrive(sb + OFF_MB_P);
        }
#undef A_LOAD
    }
    STAMP(7);

    {
        const uint32_t s2 = sb + OFF_SG2 + ch * SG2_CH;
        const uint32_t b4 = s2 + ((rr & 1) ? G2_W3 : G2_W5) + (18 + 9 * (mat & 1) + 4 * (mat >> 1) + (rr >> 1)) * 16;
        const int d8 = 6 + 8 * (mat >> 1) + rr + (mat & 1);
        const uint32_t b8 = s2 + ((rr & 1) ? ((d8 & 1) ? G2_W7O : G2_W7E) : ((d8 & 1) ? G2_W9O : G2_W9E)) + (d8 >> 1) * 16;
        const uint32_t bf = s2 + ((mat & 1) ? G2_P2O : G2_P2E) + rr * 16;
        const uint32_t pg = sb + OFF_PG2 + ch * 6144 + (32 * (q >> 1) + g) * 4;
        const int blk = 2 + role;
        const uint32_t c8 = b8 + (4 * blk - 8) * 128, c4 = b4 + (8 * blk - 8) * 144;
#define G2_STORE(ACC, BLK)                                                                                   \
        _Pragma("unroll") for (int tj = 0; tj < 4; tj += 2)                                                  \
            _Pragma("unroll") for (int br = 0; br < 2; ++br)                                                 \
                _Pragma("unroll") for (int c = 0; c < 4; ++c)                                                \
                    sts32(pg + br * 3072 + ((BLK) - 1) * 1024 + tj * 256 + (c >> 1) * 256 +                  \
                          (16 * ((q & 1) ^ (c >> 1)) + 8 * ((c & 1) ^ (q >> 1))) * 4,                        \
                          pack_bf16(ACC[tj][br][c], ACC[tj + 1][br][c]));                                    \
        __syncwarp();                                                                                         \
        if (lane == 0) mbar_arrive(sb + OFF_MB_P + 8 * (BLK));
        uint32_t fa[4], fb[4], fc[4], fd[4], fx[4][2];
#pragma unroll
        for (int ks = 0; ks < 9; ++ks) K_LOAD(k4, o4, ks);
        {
            const uint32_t msk = ((np >> 1) == q) ? ((np & 1) ? 0xFFFF0000u : 0x0000FFFFu) : 0u;
            kf[0] = lds32(ktA + KT_FIX) & msk; kf[1] = lds32(ktB + KT_FIX) & msk;
        }
#pragma unroll
        for (int ks = 0; ks < 4; ++ks) K_LOAD(k8, o8, ks);
        if (role) {
#pragma unroll
            for (int ks = 4; ks < 8; ++ks) K_LOAD(k8, o8, ks);
        }
        asm volatile("bar.sync %0, 256;\n" :: "r"(3 + role) : "memory");
        STAMP(8);
        float a8[4][2][4];
#pragma unroll
        for (int tj = 0; tj < 4; ++tj)
#pragma unroll
            for (int br = 0; br < 2; ++br) { a8[tj][br][0] = a8[tj][br][1] = a8[tj][br][2] = a8[tj][br][3] = 0.f; }
        if (role == 0) {
            ldsm4t(fa, b4 - 2 * 144); ldsm4t(fb, b4 - 144);
            asm volatile("bar.sync 7, 256;\n" ::: "memory");
            float a1[4][2][4];
#pragma unroll
            for (int tj = 0; tj < 4; ++tj)
#pragma unroll
                for (int br = 0; br < 2; ++br) { a1[tj][br][0] = a1[tj][br][1] = a1[tj][br][2] = a1[tj][br][3] = 0.f; }
            toep_block<2, 8, -2, 6, 144>(a1, k4, b4, fa, fb);
            G2_STORE(a1, 1);
            STAMP(9);
        } else {
            ldsm4t(fc, b8); ldsm4t(fd, b8 + 128);
            toep_block<1, 7, -4, -1, 128>(a8, k8, b8 + 4 * 128, fc, fd);
        }
#pragma unroll
        for (int tj = 0; tj < 4; ++tj) ldsm2t(fx[tj][0], fx[tj][1], bf + (4 * blk - 8 + tj) * 128);
        ldsm4t(fc, c8); ldsm4t(fd, c8 + 128);
        ldsm4t(fa, c4 - 8 * 144); ldsm4t(fb, c4 - 7 * 144);
#pragma unroll
        for (int tj = 0; tj < 4; ++tj) { mma_bf16_k8(a8[tj][0], fx[tj][0], fx[tj][1], kf[0]); mma_bf16_k8(a8[tj][1], fx[tj][0], fx[tj][1], kf[1]); }
        toep_block<1, 7, 0, 3, 128>(a8, k8, c8, fc, fd);
        float a4[4][2][4];
#pragma unroll
        for (int tj = 0; tj < 4; ++tj)
#pragma unroll
            for (int br = 0; br < 2; ++br) {
                a4[tj][br][0] = a8[tj][br][0]; a4[tj][br][1] = a8[tj][br][2];
                a4[tj][br][2] = a8[tj][br][1]; a4[tj][br][3] = a8[tj][br][3];
            }
        toep_block<2, 8, -8, 6, 144>(a4, k4, c4, fa, fb);
        G2_STORE(a4, blk);
        STAMP(10);
#undef G2_STORE
#undef K_LOAD
    }
    asm volatile("barrier.cluster.wait.acquire.aligned;\n" ::: "memory");
    if (role == 0) {
        asm volatile("bar.sync 10, 256;\n" ::: "memory");
        mbar_wait(sb + OFF_MB_P);
        final_block(&tm_out, sb, cl, rank, tid, 2, 11);
        STAMP(11);
        if (tid == 0) asm volatile("cp.async.bulk.wait_group.read 0;\n" ::: "memory");
    }
}

typedef CUresult (*EncodeFn)(CUtensorMap*, CUtensorMapDataType, cuuint32_t, void*, const cuuint64_t*, const cuuint64_t*,
                             const cuuint32_t*, const cuuint32_t*, CUtensorMapInterleave, CUtensorMapSwizzle,
                             CUtensorMapL2promotion, CUtensorMapFloatOOBfill);

}

extern "C" void kernel_launch(void* const* d_in, const int* in_sizes, int n_in, void* d_out, int out_size) {
    (void)in_sizes; (void)n_in; (void)out_size;
    static EncodeFn encode = nullptr;
    if (!encode) {
        void* fn = nullptr;
        cudaDriverEntryPointQueryResult qr;
        cudaGetDriverEntryPoint("cuTensorMapEncodeTiled", &fn, cudaEnableDefault, &qr);
        encode = (EncodeFn)fn;
        cudaFuncSetAttribute(fused_s4d_kernel, cudaFuncAttributeMaxDynamicSharedMemorySize, SMEM_BYTES);
    }
    CUtensorMap tin, tout;
    {
        cuuint64_t gd[3] = {DCH, 128, 16};
        cuuint64_t gs[2] = {16 * 1024, 1024};
        cuuint32_t bx[3] = {8, 128, 8};
        cuuint32_t es[3] = {1, 1, 1};
        encode(&tin, CU_TENSOR_MAP_DATA_TYPE_BFLOAT16, 3, d_in[0], gd, gs, bx, es, CU_TENSOR_MAP_INTERLEAVE_NONE,
               CU_TENSOR_MAP_SWIZZLE_NONE, CU_TENSOR_MAP_L2_PROMOTION_NONE, CU_TENSOR_MAP_FLOAT_OOB_FILL_NONE);
    }
    {
        cuuint64_t gd[4] = {DCH, 128, 2, 8};
        cuuint64_t gs[3] = {2048, 1024, 256 * 1024};
        cuuint32_t bx[4] = {8, 64, 2, 2};
        cuuint32_t es[4] = {1, 1, 1, 1};
        encode(&tout, CU_TENSOR_MAP_DATA_TYPE_BFLOAT16, 4, d_out, gd, gs, bx, es, CU_TENSOR_MAP_INTERLEAVE_NONE,
               CU_TENSOR_MAP_SWIZZLE_NONE, CU_TENSOR_MAP_L2_PROMOTION_NONE, CU_TENSOR_MAP_FLOAT_OOB_FILL_NONE);
    }
    Params prm;
    prm.u = (const __nv_bfloat16*)d_in[0];
    for (int j = 0; j < 6; ++j) {
        prm.p[0][j] = (const __nv_bfloat16*)d_in[1 + j];
        prm.p[1][j] = (const __nv_bfloat16*)d_in[8 + j];
    }
    prm.gw = (const __nv_bfloat16*)d_in[14];
    fused_s4d_kernel<<<128, NTHREADS, SMEM_BYTES, cudaStreamPerThread>>>(prm, tin, tout);
}
```

```cpp
#include <cuda_runtime.h>
#include <cuda_bf16.h>
#include <cuda_fp16.h>
#include <cuda.h>
#include <stdint.h>

#define PROFILE_CLK 0

namespace {

constexpr int LSEQ = 2048;
constexpr int DCH = 512;
constexpr int NTHREADS = 384;

constexpr int OFF_U = 0;
constexpr int OFF_ROWS = OFF_U;
constexpr int G2_W5 = 0, G2_W3 = 3776, G2_W9E = 7552, G2_W9O = G2_W9E + 1152, G2_W7E = G2_W9O + 1152 + 48,
              G2_W7O = G2_W7E + 1152 + 16, G2_P2E = G2_W7O + 1088 + 64, G2_P2O = G2_P2E + 1024, SG2_CH = 14336;
static_assert((G2_W7O - G2_W9E) % 128 == 64 && (G2_W7E + 16 - G2_W9O) % 128 == 64 && G2_P2O + 1024 <= SG2_CH, "banks");
constexpr int OFF_SG2 = 32768;
constexpr int V_H = 144 * 16, V_CH = 2 * V_H;
constexpr int OFF_V = OFF_SG2 + 4 * SG2_CH;
constexpr int OFF_S1P = OFF_V + 4 * V_CH;
constexpr int OFF_PG2 = OFF_S1P + 32768;
constexpr int OFF_GT = OFF_PG2 + 24576;
constexpr int FT_W = 8 * 71 * 16;
constexpr int OFF_FT = OFF_S1P;
constexpr int KT_W = 2960;
constexpr int KT_WD1 = 0, KT_WD4 = 288 * 8, KT_FIX = KT_WD4 + 2 * 320;
constexpr int OFF_KT = OFF_FT + 8 * FT_W;
constexpr int OFF_OUT = OFF_KT + 8 * KT_W;
constexpr int OFF_MISC = OFF_OUT + 8192;
constexpr int OFF_MB_U = OFF_MISC, OFF_MB_P = OFF_MISC + 8, OFF_MB_OUT = OFF_MISC + 40;
constexpr int OFF_TAG = OFF_MISC + 72;
constexpr int OFF_GPART = OFF_MISC + 128;
constexpr int SMEM_BYTES = OFF_GPART + 256;
static_assert(OFF_V % 128 == 0 && OFF_S1P % 128 == 0 && OFF_KT % 128 == 0 && OFF_OUT % 128 == 0, "align");
static_assert(OFF_GT + 8192 <= OFF_KT && KT_FIX + 4 <= KT_W && SMEM_BYTES <= 232448, "smem");

struct Params {
    const __nv_bfloat16* u;
    const __nv_bfloat16* p[2][6];
    const __nv_bfloat16* gw;
};

__device__ __align__(128) uint32_t g_gate[LSEQ];
__device__ uint32_t g_epoch;
__device__ uint32_t g_arrived;
#define STAMP(i) do {} while (0)
#define GSTAMP(i) do {} while (0)

__device__ __forceinline__ void ldsm4(uint32_t (&r)[4], uint32_t a) {
    asm volatile("ldmatrix.sync.aligned.m8n8.x4.shared.b16 {%0,%1,%2,%3},[%4];\n"
                 : "=r"(r[0]), "=r"(r[1]), "=r"(r[2]), "=r"(r[3]) : "r"(a) : "memory");
}
__device__ __forceinline__ void ldsm4t(uint32_t (&r)[4], uint32_t a) {
    asm volatile("ldmatrix.sync.aligned.m8n8.x4.trans.shared.b16 {%0,%1,%2,%3},[%4];\n"
                 : "=r"(r[0]), "=r"(r[1]), "=r"(r[2]), "=r"(r[3]) : "r"(a) : "memory");
}
__device__ __forceinline__ void ldsm2t(uint32_t& r0, uint32_t& r1, uint32_t a) {
    asm volatile("ldmatrix.sync.aligned.m8n8.x2.trans.shared.b16 {%0,%1},[%2];\n" : "=r"(r0), "=r"(r1) : "r"(a) : "memory");
}
__device__ __forceinline__ void mma_bf16(float (&d)[4], const uint32_t (&a)[4], uint32_t b0, uint32_t b1) {
    asm("mma.sync.aligned.m16n8k16.row.col.f32.bf16.bf16.f32 {%0,%1,%2,%3},{%4,%5,%6,%7},{%8,%9},{%0,%1,%2,%3};\n"
        : "+f"(d[0]), "+f"(d[1]), "+f"(d[2]), "+f"(d[3])
        : "r"(a[0]), "r"(a[1]), "r"(a[2]), "r"(a[3]), "r"(b0), "r"(b1));
}
__device__ __forceinline__ void mma_bf16_k8(float (&d)[4], uint32_t a0, uint32_t a1, uint32_t b0) {
    asm("mma.sync.aligned.m16n8k8.row.col.f32.bf16.bf16.f32 {%0,%1,%2,%3},{%4,%5},{%6},{%0,%1,%2,%3};\n"
        : "+f"(d[0]), "+f"(d[1]), "+f"(d[2]), "+f"(d[3]) : "r"(a0), "r"(a1), "r"(b0));
}
__device__ __forceinline__ void mma_f16(float (&d)[4], const uint32_t (&a)[4], uint32_t b0, uint32_t b1) {
    asm("mma.sync.aligned.m16n8k16.row.col.f32.f16.f16.f32 {%0,%1,%2,%3},{%4,%5,%6,%7},{%8,%9},{%0,%1,%2,%3};\n"
        : "+f"(d[0]), "+f"(d[1]), "+f"(d[2]), "+f"(d[3])
        : "r"(a[0]), "r"(a[1]), "r"(a[2]), "r"(a[3]), "r"(b0), "r"(b1));
}
__device__ __forceinline__ uint32_t lds32(uint32_t a) {
    uint32_t v; asm volatile("ld.shared.u32 %0,[%1];\n" : "=r"(v) : "r"(a) : "memory"); return v;
}
__device__ __forceinline__ uint4 lds128(uint32_t a) {
    uint4 v; asm volatile("ld.shared.v4.u32 {%0,%1,%2,%3},[%4];\n" : "=r"(v.x), "=r"(v.y), "=r"(v.z), "=r"(v.w) : "r"(a) : "memory");
    return v;
}
__device__ __forceinline__ void sts32(uint32_t a, uint32_t v) { asm volatile("st.shared.u32 [%0],%1;\n" :: "r"(a), "r"(v) : "memory"); }
__device__ __forceinline__ void sts128(uint32_t a, uint32_t x, uint32_t y, uint32_t z, uint32_t w) {
    asm volatile("st.shared.v4.u32 [%0],{%1,%2,%3,%4};\n" :: "r"(a), "r"(x), "r"(y), "r"(z), "r"(w) : "memory");
}
__device__ __forceinline__ uint32_t pack_bf16(float lo, float hi) {
    uint32_t r; asm("cvt.rn.bf16x2.f32 %0,%1,%2;\n" : "=r"(r) : "f"(hi), "f"(lo)); return r;
}
__device__ __forceinline__ uint32_t pack_f16(float lo, float hi) {
    uint32_t r; asm("cvt.rn.f16x2.f32 %0,%1,%2;\n" : "=r"(r) : "f"(hi), "f"(lo)); return r;
}
__device__ __forceinline__ uint32_t badd2(uint32_t a, uint32_t b) {
    uint32_t r; asm("add.rn.bf16x2 %0,%1,%2;\n" : "=r"(r) : "r"(a), "r"(b)); return r;
}
__device__ __forceinline__ uint32_t bmul2(uint32_t a, uint32_t b) {
    uint32_t r; asm("mul.rn.bf16x2 %0,%1,%2;\n" : "=r"(r) : "r"(a), "r"(b)); return r;
}
__device__ __forceinline__ void sts64(uint32_t a, uint32_t x, uint32_t y) {
    asm volatile("st.shared.v2.u32 [%0],{%1,%2};\n" :: "r"(a), "r"(x), "r"(y) : "memory");
}
__device__ __forceinline__ uint2 lds64(uint32_t a) {
    uint2 v; asm volatile("ld.shared.v2.u32 {%0,%1},[%2];\n" : "=r"(v.x), "=r"(v.y) : "r"(a) : "memory"); return v;
}
__device__ __forceinline__ uint32_t bfma2(uint32_t a, uint32_t b, uint32_t c) {
    uint32_t r; asm("fma.rn.bf16x2 %0,%1,%2,%3;\n" : "=r"(r) : "r"(a), "r"(b), "r"(c)); return r;
}
__device__ __forceinline__ uint32_t plo(uint32_t a, uint32_t b) { return __byte_perm(a, b, 0x5410); }
__device__ __forceinline__ uint32_t phi(uint32_t a, uint32_t b) { return __byte_perm(a, b, 0x7632); }
__device__ __forceinline__ float bf_lo(uint32_t v) { return __uint_as_float(v << 16); }
__device__ __forceinline__ float bf_hi(uint32_t v) { return __uint_as_float(v & 0xFFFF0000u); }
__device__ __forceinline__ float bf_round(float x) { return __bfloat162float(__float2bfloat16_rn(x)); }

__device__ __forceinline__ void mbar_init(uint32_t a, uint32_t cnt) {
    asm volatile("mbarrier.init.shared.b64 [%0],%1;\n" :: "r"(a), "r"(cnt) : "memory");
}
__device__ __forceinline__ void mbar_arrive(uint32_t a) {
    asm volatile("mbarrier.arrive.shared.b64 _,[%0];\n" :: "r"(a) : "memory");
}
__device__ __forceinline__ void mbar_expect(uint32_t a, uint32_t bytes) {
    asm volatile("mbarrier.arrive.expect_tx.shared.b64 _,[%0],%1;\n" :: "r"(a), "r"(bytes) : "memory");
}
__device__ __forceinline__ void mbar_wait(uint32_t a) {
    uint32_t ok = 0;
#pragma unroll 1
    for (int it = 0; it < (1 << 20) && !ok; ++it)
        asm volatile("{.reg .pred p; mbarrier.try_wait.parity.shared.b64 p,[%1],0; selp.u32 %0,1,0,p;}\n"
                     : "=r"(ok) : "r"(a) : "memory");
}
__device__ __forceinline__ void mbar_wait_cluster(uint32_t a) {
    uint32_t ok = 0;
#pragma unroll 1
    for (int it = 0; it < (1 << 20) && !ok; ++it)
        asm volatile("{.reg .pred p; mbarrier.try_wait.parity.acquire.cluster.shared.b64 p,[%1],0; selp.u32 %0,1,0,p;}\n"
                     : "=r"(ok) : "r"(a) : "memory");
}

struct c32 { float x, y; };
__device__ __forceinline__ c32 csq(c32 z) { c32 r; r.x = fmaf(z.x, z.x, -(z.y * z.y)); r.y = (z.x + z.x) * z.y; return r; }
__device__ __forceinline__ c32 cexp_seed(float al2, float ai, float x) {
    float m, s, c, th = ai * x, e = al2 * x;
    asm("ex2.approx.ftz.f32 %0,%1;\n" : "=f"(m) : "f"(e));
    asm("sin.approx.ftz.f32 %0,%1;\n" : "=f"(s) : "f"(th));
    asm("cos.approx.ftz.f32 %0,%1;\n" : "=f"(c) : "f"(th));
    c32 r; r.x = m * c; r.y = m * s; return r;
}
typedef unsigned long long pc;
__device__ __forceinline__ pc mk64(uint32_t re, uint32_t im) { pc r; asm("mov.b64 %0,{%1,%2};\n" : "=l"(r) : "r"(re), "r"(im)); return r; }
__device__ __forceinline__ pc mkp(c32 a, c32 b) {
    pc r;
    asm("{.reg .b32 x,y; cvt.rn.f16x2.f32 x,%2,%1; cvt.rn.f16x2.f32 y,%4,%3; mov.b64 %0,{x,y};}\n"
        : "=l"(r) : "f"(a.x), "f"(b.x), "f"(a.y), "f"(b.y));
    return r;
}
__device__ __forceinline__ pc pmul(pc z, pc w) {
    pc r;
    asm("{.reg .b32 zr,zi,wr,wi,t0,t1,n; mov.b64 {zr,zi},%1; mov.b64 {wr,wi},%2;\n"
        "mul.rn.f16x2 t0,zr,wr; mul.rn.f16x2 t1,zi,wr; neg.f16x2 n,zi;\n"
        "fma.rn.f16x2 t0,n,wi,t0; fma.rn.f16x2 t1,zr,wi,t1; mov.b64 %0,{t0,t1};}\n"
        : "=l"(r) : "l"(z), "l"(w));
    return r;
}
__device__ __forceinline__ void stp(uint32_t a, pc v) {
    asm volatile("{.reg .b32 x,y; mov.b64 {x,y},%1; stmatrix.sync.aligned.m8n8.x2.shared.b16 [%0],{x,y};}\n"
                 :: "r"(a), "l"(v) : "memory");
}
__device__ __forceinline__ void mma_f16p(float (&d)[4], const uint32_t (&a)[4], pc b) {
    asm("{.reg .b32 x,y; mov.b64 {x,y},%8;\n"
        "mma.sync.aligned.m16n8k16.row.col.f32.f16.f16.f32 {%0,%1,%2,%3},{%4,%5,%6,%7},{x,y},{%0,%1,%2,%3};}\n"
        : "+f"(d[0]), "+f"(d[1]), "+f"(d[2]), "+f"(d[3]) : "r"(a[0]), "r"(a[1]), "r"(a[2]), "r"(a[3]), "l"(b));
}

__device__ __forceinline__ void store_pair(uint32_t a0, uint32_t a1, uint32_t v0, uint32_t v1, uint32_t v2, uint32_t v3,
                                           uint32_t v4, uint32_t v5, uint32_t v6, uint32_t v7) {
    sts128(a0, plo(v0, v1), plo(v2, v3), plo(v4, v5), plo(v6, v7));
    sts128(a1, phi(v0, v1), phi(v2, v3), phi(v4, v5), phi(v6, v7));
}

__device__ __forceinline__ void wgmma_n128(float (&d)[64], uint32_t a0, uint32_t a1, uint32_t a2, uint32_t a3, uint32_t dlo,
                                           int accumulate) {
    asm volatile("{.reg .pred p; .reg .b64 ds; setp.ne.s32 p,%69,0; mov.b64 ds,{%68,%70};\n"
                 "wgmma.mma_async.sync.aligned.m64n128k16.f32.bf16.bf16 {%0,%1,%2,%3,%4,%5,%6,%7,%8,%9,%10,%11,%12,%13,%14,%15,%16,%17,%18,%19,%20,%21,%22,%23,%24,%25,%26,%27,%28,%29,%30,%31,%32,%33,%34,%35,%36,%37,%38,%39,%40,%41,%42,%43,%44,%45,%46,%47,%48,%49,%50,%51,%52,%53,%54,%55,%56,%57,%58,%59,%60,%61,%62,%63},\n"
                 "{%64,%65,%66,%67},ds,p,1,1,0;}\n"
                 : "+f"(d[0]),"+f"(d[1]),"+f"(d[2]),"+f"(d[3]),"+f"(d[4]),"+f"(d[5]),"+f"(d[6]),"+f"(d[7]),"+f"(d[8]),"+f"(d[9]),"+f"(d[10]),"+f"(d[11]),"+f"(d[12]),"+f"(d[13]),"+f"(d[14]),"+f"(d[15]),"+f"(d[16]),"+f"(d[17]),"+f"(d[18]),"+f"(d[19]),"+f"(d[20]),"+f"(d[21]),"+f"(d[22]),"+f"(d[23]),"+f"(d[24]),"+f"(d[25]),"+f"(d[26]),"+f"(d[27]),"+f"(d[28]),"+f"(d[29]),"+f"(d[30]),"+f"(d[31]),"+f"(d[32]),"+f"(d[33]),"+f"(d[34]),"+f"(d[35]),"+f"(d[36]),"+f"(d[37]),"+f"(d[38]),"+f"(d[39]),"+f"(d[40]),"+f"(d[41]),"+f"(d[42]),"+f"(d[43]),"+f"(d[44]),"+f"(d[45]),"+f"(d[46]),"+f"(d[47]),"+f"(d[48]),"+f"(d[49]),"+f"(d[50]),"+f"(d[51]),"+f"(d[52]),"+f"(d[53]),"+f"(d[54]),"+f"(d[55]),"+f"(d[56]),"+f"(d[57]),"+f"(d[58]),"+f"(d[59]),"+f"(d[60]),"+f"(d[61]),"+f"(d[62]),"+f"(d[63])
                 : "r"(a0), "r"(a1), "r"(a2), "r"(a3), "r"(dlo), "r"(accumulate), "n"(128 >> 4));
}

template <int TS, int KMAX, int LO, int HI, int STRIDE>
__device__ __forceinline__ void toep_block(float (&acc)[4][2][4], const uint32_t (&kb)[KMAX + 1][2][2], uint32_t base,
                                           const uint32_t (&f0)[4], const uint32_t (&f1)[4]) {
    uint32_t fr[4][4];
#pragma unroll
    for (int j = 0; j < 4; ++j) { fr[0][j] = f0[j]; fr[1][j] = f1[j]; }
    if (LO + 2 <= HI) ldsm4t(fr[2], base + (uint32_t)((LO + 2) * STRIDE));
#pragma unroll
    for (int loc = LO; loc <= HI; ++loc) {
        if (loc + 3 <= HI) ldsm4t(fr[(loc + 3 - LO) & 3], base + (loc + 3) * STRIDE);
#pragma unroll
        for (int tj = 0; tj < 4; ++tj) {
            const int ks = TS * tj - loc;
            if (ks >= 0 && ks <= KMAX) {
                mma_bf16(acc[tj][0], fr[(loc - LO) & 3], kb[ks][0][0], kb[ks][0][1]);
                mma_bf16(acc[tj][1], fr[(loc - LO) & 3], kb[ks][1][0], kb[ks][1][1]);
            }
        }
    }
}

__device__ __forceinline__ uint32_t gate_word(float s) {
    float sb = bf_round(s);
    float g = bf_round(1.0f / (1.0f + expf(-sb)));
    float o = bf_round(1.0f - g);
    return ((__float_as_uint(g) >> 16) | (__float_as_uint(o) & 0xFFFF0000u)) & 0x7FFF7FFFu;
}

__device__ __forceinline__ void final_block(const CUtensorMap* tm, uint32_t sb, int cl, int rank, int un, int b, int barid) {
    uint32_t oaddr, obar;
    asm("mapa.shared::cluster.u32 %0,%1,%2;\n" : "=r"(oaddr) : "r"(sb + OFF_OUT + b * 2048 + un * 16), "r"(rank ^ 1));
    asm("mapa.shared::cluster.u32 %0,%1,%2;\n" : "=r"(obar) : "r"(sb + OFF_MB_OUT + 8 * b), "r"(rank ^ 1));
    const uint32_t orow = sb + OFF_ROWS + b * 4096 + (un >> 6) * 2048 + (un & 63) * 16;
    const uint32_t sw = ((2 * un) ^ ((un >> 1) & 0x18)) * 4 + b * 1024;
    const uint32_t psel = rank ? 0x7632u : 0x5410u;
    uint2 ya[4], yb[4];
    const uint4 gw = lds128(sb + OFF_GT + (b * 256 + 2 * un) * 8);
#pragma unroll
    for (int c = 0; c < 4; ++c) {
        ya[c] = lds64(sb + OFF_S1P + c * 8192 + sw);
        yb[c] = lds64(sb + OFF_S1P + c * 8192 + 4096 + sw);
    }
    if (b > 0) {
        mbar_wait(sb + OFF_MB_P + 8 * b);
#pragma unroll
        for (int c = 0; c < 4; ++c) {
            const uint2 za = lds64(sb + OFF_PG2 - 1024 + c * 6144 + sw);
            const uint2 zb = lds64(sb + OFF_PG2 - 1024 + c * 6144 + 3072 + sw);
            ya[c].x = badd2(ya[c].x, za.x); ya[c].y = badd2(ya[c].y, za.y);
            yb[c].x = badd2(yb[c].x, zb.x); yb[c].y = badd2(yb[c].y, zb.y);
        }
    }
    uint32_t o0[4], o1[4];
#pragma unroll
    for (int c = 0; c < 4; ++c) {
        o0[c] = bfma2(ya[c].x, gw.x, bmul2(yb[c].x, gw.y));
        o1[c] = bfma2(ya[c].y, gw.z, bmul2(yb[c].y, gw.w));
    }
    asm volatile("st.async.weak.shared::cluster.mbarrier::complete_tx::bytes.v4.b32 [%0],{%1,%2,%3,%4},[%5];\n"
                 :: "r"(oaddr), "r"(__byte_perm(o0[0], o0[1], psel ^ 0x2222u)), "r"(__byte_perm(o0[2], o0[3], psel ^ 0x2222u)),
                    "r"(__byte_perm(o1[0], o1[1], psel ^ 0x2222u)), "r"(__byte_perm(o1[2], o1[3], psel ^ 0x2222u)),
                    "r"(obar) : "memory");
    sts64(orow + rank * 8, __byte_perm(o0[0], o0[1], psel), __byte_perm(o0[2], o0[3], psel));
    sts64(orow + 1024 + rank * 8, __byte_perm(o1[0], o1[1], psel), __byte_perm(o1[2], o1[3], psel));
    mbar_wait_cluster(sb + OFF_MB_OUT + 8 * b);
    const uint4 pe = lds128(sb + OFF_OUT + b * 2048 + un * 16);
    sts64(orow + 8 - rank * 8, pe.x, pe.y);
    sts64(orow + 1032 - rank * 8, pe.z, pe.w);
    asm volatile("fence.proxy.async.shared::cta;\n" ::: "memory");
    asm volatile("bar.sync %0, 128;\n" :: "r"(barid) : "memory");
    if (un == 0) {
        asm volatile("cp.async.bulk.tensor.4d.global.shared::cta.bulk_group [%0,{%1,%2,%3,%4}],[%5];\n"
                     :: "l"(tm), "r"(8 * cl), "r"(64 * rank), "r"(0), "r"(2 * b), "r"(sb + OFF_ROWS + b * 4096) : "memory");
        asm volatile("cp.async.bulk.commit_group;\n" ::: "memory");
    }
}

__global__ void __cluster_dims__(2, 1, 1) __launch_bounds__(NTHREADS, 1)
fused_s4d_kernel(const __grid_constant__ Params prm, const __grid_constant__ CUtensorMap tm_in,
                 const __grid_constant__ CUtensorMap tm_out) {
    extern __shared__ __align__(1024) unsigned char smem[];
    const uint32_t sb = (uint32_t)__cvta_generic_to_shared(smem);
    const int tid = threadIdx.x, warp = tid >> 5, lane = tid & 31;
    const int rank = blockIdx.x & 1, cl = blockIdx.x >> 1;
    if (warp != 8) asm volatile("barrier.cluster.arrive.relaxed.aligned;\n" ::: "memory");
    STAMP(0);
    if (tid == 128) GSTAMP(0);

    if (warp >= 8) {
        const int un = tid - 256;
        if (warp == 8) {
            if (lane == 0) {
                asm volatile("prefetch.tensormap [%0];\n" :: "l"(&tm_in) : "memory");
                asm volatile("prefetch.tensormap [%0];\n" :: "l"(&tm_out) : "memory");
                mbar_init(sb + OFF_MB_U, 1);
                mbar_init(sb + OFF_MB_P, 16);
#pragma unroll
                for (int i = 1; i < 4; ++i) mbar_init(sb + OFF_MB_P + 8 * i, 4);
#pragma unroll
                for (int i = 0; i < 4; ++i) mbar_init(sb + OFF_MB_OUT + 8 * i, 1);
                mbar_expect(sb + OFF_MB_U, 32768);
#pragma unroll
                for (int i = 0; i < 4; ++i) mbar_expect(sb + OFF_MB_OUT + 8 * i, 2048);
                asm volatile("fence.mbarrier_init.release.cluster;\n" ::: "memory");
                asm volatile("fence.proxy.async.shared::cta;\n" ::: "memory");
            }
            __syncwarp();
            asm volatile("barrier.cluster.arrive.relaxed.aligned;\n" ::: "memory");
        }
        asm volatile("barrier.cluster.wait.acquire.aligned;\n" ::: "memory");
        if (un == 0) {
            asm volatile("cp.async.bulk.tensor.3d.shared::cluster.global.mbarrier::complete_tx::bytes.multicast::cluster "
                         "[%0],[%1,{%2,%3,%4}],[%5],%6;\n"
                         :: "r"(sb + OFF_U + rank * 16384), "l"(&tm_in), "r"(8 * cl), "r"(0), "r"(8 * rank), "r"(sb + OFF_MB_U),
                            "h"((uint16_t)3) : "memory");
        }
        STAMP(9);
        {
            const uint32_t a2 = sb + OFF_SG2 + (warp - 8) * SG2_CH;
            sts128(a2 + (lane < 16 ? G2_W5 : G2_W3) + ((lane & 15) + ((lane >> 3) & 1)) * 16, 0, 0, 0, 0);
            if (lane < 16) sts128(a2 + (lane < 4 ? G2_W9E : lane < 8 ? G2_W9O : lane < 12 ? G2_W7E : G2_W7O) + (lane & 3) * 16, 0, 0, 0, 0);
            sts128(sb + OFF_V + (warp - 8) * V_CH + (lane >> 4) * V_H + (lane & 15) * 16, 0, 0, 0, 0);
        }
        const int g = lane >> 2, q = lane & 3;
        uint32_t epoch = 0;
        if (warp == 8) asm volatile("ld.relaxed.gpu.global.u32 %0,[%1];\n" : "=r"(epoch) : "l"(&g_epoch) : "memory");
        uint4 gx[8], gwv[4];
        const uint4* ur = reinterpret_cast<const uint4*>(prm.u) + (size_t)(blockIdx.x * 16 + g) * 64 + (warp - 8) * 16 + q;
        const uint4* wr = reinterpret_cast<const uint4*>(prm.gw) + (warp - 8) * 16 + q;
#pragma unroll
        for (int j = 0; j < 4; ++j) { gx[2 * j] = __ldg(ur + 4 * j); gx[2 * j + 1] = __ldg(ur + 8 * 64 + 4 * j); gwv[j] = __ldg(wr + 4 * j); }
        {
            float gs[4] = {0.f, 0.f, 0.f, 0.f}, gt[4] = {0.f, 0.f, 0.f, 0.f};
#pragma unroll
            for (int j = 0; j < 4; ++j) {
                uint32_t a[4], b[4];
                a[0] = bmul2(gx[2 * j].x, gwv[j].x); a[1] = bmul2(gx[2 * j + 1].x, gwv[j].x);
                a[2] = bmul2(gx[2 * j].y, gwv[j].y); a[3] = bmul2(gx[2 * j + 1].y, gwv[j].y);
                b[0] = bmul2(gx[2 * j].z, gwv[j].z); b[1] = bmul2(gx[2 * j + 1].z, gwv[j].z);
                b[2] = bmul2(gx[2 * j].w, gwv[j].w); b[3] = bmul2(gx[2 * j + 1].w, gwv[j].w);
                mma_bf16(gs, a, 0x3F803F80u, 0x3F803F80u);
                mma_bf16(gt, b, 0x3F803F80u, 0x3F803F80u);
            }
            if (q == 0) {
                sts32(sb + OFF_GPART + ((warp - 8) * 16 + g) * 4, __float_as_uint(gs[0] + gt[0]));
                sts32(sb + OFF_GPART + ((warp - 8) * 16 + g + 8) * 4, __float_as_uint(gs[2] + gt[2]));
            }
            asm volatile("bar.sync 1, 128;\n" ::: "memory");
            if (warp == 8) {
                const uint32_t tg = (epoch + 1u) & 3u;
                if (lane < 16) {
                    float t = 0.f;
#pragma unroll
                    for (int w = 0; w < 4; ++w) t += __uint_as_float(lds32(sb + OFF_GPART + (w * 16 + lane) * 4));
                    const uint32_t wd = gate_word(t) | ((tg & 1u) << 15) | ((tg & 2u) << 30);
                    asm volatile("st.relaxed.gpu.global.u32 [%0],%1;\n" :: "l"(&g_gate[blockIdx.x * 16 + lane]), "r"(wd) : "memory");
                }
                if (lane == 0) {
                    sts32(sb + OFF_TAG, ((tg & 1u) << 15) | ((tg & 2u) << 30));
                    sts32(sb + OFF_TAG + 4, epoch + 1u);
                }
            }
        }
        STAMP(10);
        mbar_wait(sb + OFF_MB_U);
        STAMP(2);
        {
            const uint32_t ua = sb + OFF_U + un * 16 + rank * 8;
            uint2 v[16];
#pragma unroll
            for (int j = 0; j < 16; ++j) v[j] = lds64(ua + j * 2048);
            const uint32_t a = sb + OFF_V + (16 + un) * 16;
            store_pair(a, a + V_CH, v[0].x, v[1].x, v[2].x, v[3].x, v[4].x, v[5].x, v[6].x, v[7].x);
            store_pair(a + V_H, a + V_H + V_CH, v[8].x, v[9].x, v[10].x, v[11].x, v[12].x, v[13].x, v[14].x, v[15].x);
            store_pair(a + 2 * V_CH, a + 3 * V_CH, v[0].y, v[1].y, v[2].y, v[3].y, v[4].y, v[5].y, v[6].y, v[7].y);
            store_pair(a + V_H + 2 * V_CH, a + V_H + 3 * V_CH, v[8].y, v[9].y, v[10].y, v[11].y, v[12].y, v[13].y, v[14].y, v[15].y);
        }
        asm volatile("fence.proxy.async.shared::cta;\n" ::: "memory");
        asm volatile("bar.arrive 2, 288;\n" ::: "memory");
        STAMP(3);
        asm volatile("bar.sync 9, 384;\n" ::: "memory");
#pragma unroll 1
        for (int it = 0; it < 3; ++it) {
            if (it == 2) {
                asm volatile("bar.arrive 3, 256;\n" ::: "memory");
                STAMP(4);
            }
            const int rho = it * 32 + lane;
            const uint32_t va = sb + OFF_V + (warp - 8) * V_CH + (16 + rho) * 16;
            const uint4 e0 = lds128(va + V_H - 16), e1 = lds128(va), e2 = lds128(va + V_H), e3 = lds128(va + 16);
            const uint32_t E[13] = {e0.z, e0.w, e1.x, e1.y, e1.z, e1.w, e2.x, e2.y, e2.z, e2.w, e3.x, e3.y, e3.z};
            uint32_t O[12], P2[12], W3[12], P4[11], W5[11];
#pragma unroll
            for (int k = 0; k < 12; ++k) { O[k] = __byte_perm(E[k], E[k + 1], 0x5432); P2[k] = badd2(E[k], O[k]); }
#pragma unroll
            for (int k = 1; k < 12; ++k) W3[k] = badd2(O[k - 1], P2[k]);
#pragma unroll
            for (int k = 0; k < 11; ++k) P4[k] = badd2(P2[k], P2[k + 1]);
#pragma unroll
            for (int k = 2; k < 11; ++k) W5[k] = badd2(P4[k - 1], E[k + 1]);
            const uint32_t s2a = sb + OFF_SG2 + (warp - 8) * SG2_CH;
            const int c5 = 2 * rho + 16;
            const uint32_t a5 = s2a + G2_W5 + (c5 + (c5 >> 3)) * 16, a3 = a5 + (G2_W3 - G2_W5);
            sts128(a5, W5[2], W5[3], W5[4], W5[5]); sts128(a5 + 16, W5[6], W5[7], W5[8], W5[9]);
            sts128(a3, W3[4], W3[5], W3[6], W3[7]); sts128(a3 + 16, W3[8], W3[9], W3[10], W3[11]);
            if (it < 2) {
                uint32_t W7[8], W9[8];
#pragma unroll
                for (int k = 0; k < 8; ++k) { W7[k] = badd2(W3[k + 1], P4[k + 2]); W9[k] = badd2(P4[k], W5[k + 3]); }
                const uint32_t a9 = s2a + (rho + 4) * 16, ap = s2a + rho * 16;
                sts128(a9 + G2_W9E, W9[0], W9[1], W9[2], W9[3]); sts128(a9 + G2_W9O, W9[4], W9[5], W9[6], W9[7]);
                sts128(a9 + G2_W7E, W7[0], W7[1], W7[2], W7[3]); sts128(a9 + G2_W7O, W7[4], W7[5], W7[6], W7[7]);
                sts128(ap + G2_P2E, P2[0], P2[1], P2[2], P2[3]); sts128(ap + G2_P2O, P2[4], P2[5], P2[6], P2[7]);
                if (rho == 0) {
                    const uint32_t n12 = plo(E[2], P2[2]);
                    sts128(a5 - 32, 0, 0, 0, n12);
                    sts128(a3 - 32, 0, W3[1], W3[2], W3[3]);
                    sts128(a9 + G2_W9O - 16, 0, 0, n12, __byte_perm(W3[2], P4[2], 0x5432));
                    sts128(a9 + G2_W7O - 16, 0, 0, E[2] << 16, __byte_perm(P2[2], W3[2], 0x7610));
                }
            }
        }
        asm volatile("bar.arrive 4, 256;\n" ::: "memory");
        {
            const int uc = un;
            const uint32_t tagw = lds32(sb + OFF_TAG);
            bool done = false;
            const int tb0 = (uc >> 5) * 256 + (uc & 31) * 4;
#pragma unroll 1
            for (int tries = 0; tries < 8192 && !done; ++tries) {
                uint4 v[4];
#pragma unroll
                for (int i = 0; i < 4; ++i)
                    asm volatile("ld.relaxed.gpu.global.v4.u32 {%0,%1,%2,%3},[%4];\n"
                                 : "=r"(v[i].x), "=r"(v[i].y), "=r"(v[i].z), "=r"(v[i].w)
                                 : "l"(&g_gate[tb0 + (i >> 1) * 1024 + (i & 1) * 128]) : "memory");
                uint32_t bad = 0;
#pragma unroll
                for (int i = 0; i < 4; ++i)
                    bad |= (v[i].x ^ tagw) | (v[i].y ^ tagw) | (v[i].z ^ tagw) | (v[i].w ^ tagw);
                done = __all_sync(0xffffffffu, (bad & 0x80008000u) == 0);
                if (done) {
#pragma unroll
                    for (int i = 0; i < 2; ++i) {
                        const uint4 a = v[2 * i], b = v[2 * i + 1];
                        const uint32_t d = sb + OFF_GT + (i * 512 + uc * 4) * 8;
                        sts128(d, plo(a.x, b.x) & 0x7FFF7FFFu, phi(a.x, b.x) & 0x7FFF7FFFu, plo(a.y, b.y) & 0x7FFF7FFFu, phi(a.y, b.y) & 0x7FFF7FFFu);
                        sts128(d + 16, plo(a.z, b.z) & 0x7FFF7FFFu, phi(a.z, b.z) & 0x7FFF7FFFu, plo(a.w, b.w) & 0x7FFF7FFFu, phi(a.w, b.w) & 0x7FFF7FFFu);
                    }
                } else {
                    __nanosleep(64);
                }
            }
            if (!done) {
#pragma unroll 1
                for (int k = 0; k < 512; ++k) {
                    const int t = (k >> 8) * 1024 + (uc >> 5) * 256 + (k & 255);
                    float s = 0.f;
#pragma unroll 1
                    for (int j = 0; j < 8; ++j) {
                        const uint32_t pr = bmul2(reinterpret_cast<const uint32_t*>(prm.u)[t * 256 + j * 32 + lane],
                                                  reinterpret_cast<const uint32_t*>(prm.gw)[j * 32 + lane]);
                        s += bf_lo(pr) + bf_hi(pr);
                    }
#pragma unroll
                    for (int o = 16; o > 0; o >>= 1) s += __shfl_xor_sync(0xffffffffu, s, o);
                    if (lane == 0) {
                        const uint32_t wd = gate_word(s);
                        const uint32_t d = sb + OFF_GT + ((t >> 8) * 128 + (t & 127)) * 8 + ((t >> 7) & 1) * 2;
                        asm volatile("st.shared.u16 [%0],%1;\n" :: "r"(d), "h"((uint16_t)(wd & 0xFFFFu)) : "memory");
                        asm volatile("st.shared.u16 [%0],%1;\n" :: "r"(d + 4), "h"((uint16_t)(wd >> 16)) : "memory");
                    }
                }
            }
        }
        asm volatile("bar.sync 1, 128;\n" ::: "memory");
        STAMP(11);
        if (un == 32) {
            asm volatile("{.reg .pred p; .reg .u32 n;\n"
                         "atom.relaxed.gpu.global.inc.u32 n,[%0],%2;\n"
                         "setp.eq.u32 p,n,%2;\n"
                         "@p st.relaxed.gpu.global.u32 [%1],%3;}\n"
                         :: "l"(&g_arrived), "l"(&g_epoch), "r"(gridDim.x - 1), "r"(lds32(sb + OFF_TAG + 4)) : "memory");
        }
        __syncwarp();
        asm volatile("bar.arrive 10, 256;\n" ::: "memory");
        mbar_wait(sb + OFF_MB_P);
#pragma unroll 1
        for (int b = 0; b < 4; b += (b == 1) ? 2 : 1) {
            final_block(&tm_out, sb, cl, rank, un, b, 1);
            STAMP(5 + b);
        }
        if (un == 0) {
            asm volatile("cp.async.bulk.wait_group.read 0;\n" ::: "memory");
            STAMP(13);
            GSTAMP(1);
        }
        return;
    }

    const int ch = warp & 3, role = warp >> 2;
    const int chg = 8 * cl + 4 * rank + ch;
    const int g = lane >> 2, q = lane & 3;

    uint2 pLA, pAI, pCR, pCI;
    {
        const size_t o = (size_t)chg * 128 + lane * 4;
        pLA = __ldg(reinterpret_cast<const uint2*>(prm.p[role][0] + o));
        pAI = __ldg(reinterpret_cast<const uint2*>(prm.p[role][1] + o));
        pCR = __ldg(reinterpret_cast<const uint2*>(prm.p[role][2] + o));
        pCI = __ldg(reinterpret_cast<const uint2*>(prm.p[role][3] + o));
    }
    const float log_dt = __bfloat162float(prm.p[role][4][chg]);
    const float dskip = __bfloat162float(prm.p[role][5][chg]);

    const uint32_t kt = sb + OFF_KT + warp * KT_W;
    {
        if (lane < 30) sts64(kt + KT_WD1 + (lane < 14 ? lane : 258 + lane) * 8, 0u, 0u);
        const uint32_t z2 = kt + KT_WD4 + (lane < 7 ? lane : 64 + lane) * 4;
        if (lane < 16) { sts32(z2, 0u); sts32(z2 + 320, 0u); }
    }
    float dt = 0.f, fscale = 0.f, cinv = 0.f, f0 = 0.f;
    float dk[5][4];
#pragma unroll
    for (int j = 0; j < 5; ++j) { dk[j][0] = dk[j][1] = dk[j][2] = dk[j][3] = 0.f; }
    {
        const uint32_t tb = sb + OFF_FT + warp * FT_W;
        const int mat = lane >> 3, rr = lane & 7;
        const uint32_t stb = tb + (71 * rr + 8 * (mat & 1)) * 16, stc = tb + (71 * rr + 64 + (mat & 1)) * 16;
        const uint32_t ld0 = tb + ((mat & 1) ? 64 + (mat >> 1) : 8 * (mat >> 1) + rr) * 16;
        const uint32_t ld1 = tb + (16 + 8 * mat + rr) * 16;
        const uint32_t ld2 = tb + ((mat & 2) ? 64 + mat : 48 + 8 * mat + rr) * 16;
        const uint32_t ld3 = tb + (71 * (mat >> 1) + 68 + (mat & 1)) * 16;
#pragma unroll
        for (int r = 0; r < 2; ++r) {
            uint32_t wLA = 0u, wAI = 0u, wCR = 0u, wCI = 0u;
            if (r == 0) {
                dt = bf_round(expf(log_dt));
                uint32_t m = max(max(max(pCR.x & 0x7F80u, (pCR.x >> 16) & 0x7F80u), max(pCR.y & 0x7F80u, (pCR.y >> 16) & 0x7F80u)),
                                 max(max(pCI.x & 0x7F80u, (pCI.x >> 16) & 0x7F80u), max(pCI.y & 0x7F80u, (pCI.y >> 16) & 0x7F80u)));
                m = __reduce_max_sync(0xffffffffu, m) >> 7;
                m = min(max(m, 1u), 253u);
                cinv = __uint_as_float((254u - m) << 23);
                fscale = 2.0f * dt * __uint_as_float(m << 23);
                wLA = pLA.x; wAI = pAI.x; wCR = pCR.x; wCI = pCI.x;
                STAMP(1);
            } else if (r == 1) {
                f0 = (bf_lo(pCR.x) + bf_hi(pCR.x)) + (bf_lo(pCR.y) + bf_hi(pCR.y));
#pragma unroll
                for (int o = 16; o > 0; o >>= 1) f0 += __shfl_xor_sync(0xffffffffu, f0, o);
                f0 = fmaf(2.0f * dt, f0, dskip);
                wLA = pLA.y; wAI = pAI.y; wCR = pCR.y; wCI = pCI.y;
            }
            float ea, eb;
            asm("ex2.approx.ftz.f32 %0,%1;\n" : "=f"(ea) : "f"(bf_lo(wLA) * 1.4426950408889634f));
            asm("ex2.approx.ftz.f32 %0,%1;\n" : "=f"(eb) : "f"(bf_hi(wLA) * 1.4426950408889634f));
            const uint32_t e2 = pack_bf16(ea, eb);
            const float ala = (-bf_lo(e2) * dt) * 1.4426950408889634f, alb = (-bf_hi(e2) * dt) * 1.4426950408889634f;
            const float aia = bf_lo(wAI) * dt, aib = bf_hi(wAI) * dt;
            const pc C = mk64(pack_f16(bf_lo(wCR) * cinv, bf_hi(wCR) * cinv), pack_f16(bf_lo(wCI) * cinv, bf_hi(wCI) * cinv));
            {
                c32 a = cexp_seed(ala, -aia, 16.f), b = cexp_seed(alb, -aib, 16.f);
                const pc f1 = mkp(a, b); a = csq(a); b = csq(b);
                const pc f2 = mkp(a, b); a = csq(a); b = csq(b);
                const pc f4 = mkp(a, b); a = csq(a); b = csq(b);
                stp(stb, 0x3C003C00ull);
                stp(stb + 16, f1); stp(stb + 32, f2); stp(stb + 64, f4); stp(stc, mkp(a, b));
                c32 a256 = csq(a), b256 = csq(b);
                a256.y = -a256.y; b256.y = -b256.y;
                const pc f3 = pmul(f1, f2);
                stp(stb + 48, f3); stp(stb + 80, pmul(f1, f4)); stp(stb + 96, pmul(f2, f4)); stp(stb + 112, pmul(f3, f4));
                a = cexp_seed(ala, aia, 1.f); b = cexp_seed(alb, aib, 1.f);
                const pc w1 = mkp(a, b); a = csq(a); b = csq(b);
                const pc w2 = mkp(a, b); a = csq(a); b = csq(b);
                const pc w4 = mkp(a, b); a = csq(a); b = csq(b);
                const pc w8 = mkp(a, b);
                stp(stc + 32, w1);
                pc D[4];
                D[0] = pmul(C, w1); D[1] = pmul(D[0], w2); D[2] = pmul(D[0], w4); D[3] = pmul(D[1], w4);
#pragma unroll
                for (int j = 0; j < 4; ++j) { stp(stb + 256 + 16 * j, D[j]); stp(stb + 320 + 16 * j, pmul(D[j], w8)); }
                a = a256; b = b256;
                const pc w256 = mkp(a, b); a = csq(a); b = csq(b);
                const pc w512 = mkp(a, b); a = csq(a); b = csq(b);
                const pc w1024 = mkp(a, b);
                stp(stc + 64, w256);
                D[0] = pmul(C, w4); D[1] = pmul(C, w8); D[2] = pmul(D[0], w8); D[3] = pmul(D[1], w8);
#pragma unroll
                for (int j = 0; j < 4; ++j) {
                    const pc t = pmul(D[j], w512);
                    stp(stb + 512 + 16 * j, t); stp(stb + 576 + 16 * j, pmul(t, w256));
                }
#pragma unroll
                for (int j = 0; j < 2; ++j) {
                    const pc t = pmul(D[2 * j + 1], w1024), t2 = pmul(t, w256);
                    stp(stb + 768 + 16 * j, t); stp(stb + 800 + 16 * j, t2);
                    stp(stb + 832 + 16 * j, pmul(t, w512)); stp(stb + 864 + 16 * j, pmul(t2, w512));
                }
            }
            __syncwarp();
#pragma unroll
            for (int s = 0; s < 8; s += 2) {
                uint32_t W[4];
                ldsm4(W, ld3 + s * 1136);
#pragma unroll
                for (int h = 0; h < 2; ++h) {
                    uint32_t L0[4], L1[4], L2[4];
                    ldsm4(L0, ld0 + (s + h) * 1136); ldsm4(L1, ld1 + (s + h) * 1136); ldsm4(L2, ld2 + (s + h) * 1136);
                    uint32_t A[4];
                    A[0] = L0[0]; A[2] = L0[2];
                    asm("{.reg .b32 t0,t1,n; mul.rn.f16x2 t0,%2,%4; mul.rn.f16x2 t1,%3,%4; neg.f16x2 n,%3;\n"
                        "fma.rn.f16x2 %0,n,%5,t0; fma.rn.f16x2 %1,%2,%5,t1;}\n"
                        : "=r"(A[1]), "=r"(A[3]) : "r"(L0[0]), "r"(L0[2]), "r"(L0[1]), "r"(L0[3]));
                    const pc t1 = pmul(mk64(L1[0], L1[1]), mk64(L2[2], L2[3]));
                    const pc t2 = pmul(t1, mk64(W[2 * h], W[2 * h + 1]));
                    mma_f16(dk[0], A, L1[0], L1[1]);
                    mma_f16(dk[3], A, L1[2], L1[3]);
                    mma_f16(dk[4], A, L2[0], L2[1]);
                    mma_f16p(dk[1], A, t1);
                    mma_f16p(dk[2], A, t2);
                }
            }
            __syncwarp();
        }
    }
    STAMP(2);

    {
        const bool last = (lane == 31);
#pragma unroll
        for (int j = 0; j < 5; ++j)
#pragma unroll
            for (int c = 0; c < 4; ++c) dk[j][c] *= fscale;
        const float f256 = dk[1][3], f512 = dk[2][3], f1024 = dk[3][3];
        if (last) { dk[2][2] -= f512; dk[2][3] = 0.f; }
        const float n0 = __shfl_sync(0xffffffffu, dk[0][0], (lane + 1) & 31), n1 = __shfl_sync(0xffffffffu, dk[0][2], (lane + 1) & 31);
        const float p0 = __shfl_sync(0xffffffffu, lane == 31 ? f256 : dk[2][1], (lane + 31) & 31);
        const float p1 = __shfl_sync(0xffffffffu, lane == 31 ? dk[2][1] : dk[2][3], (lane + 31) & 31);
#pragma unroll
        for (int hh = 0; hh < 2; ++hh) {
            const float a = dk[0][2 * hh], b = dk[1][2 * hh], c = dk[0][2 * hh + 1], d = dk[1][2 * hh + 1];
            const float an = hh == 0 ? (last ? n1 : n0) : (last ? d : n1);
            const uint32_t wa = kt + KT_WD1 + (16 + 4 * lane + 128 * hh) * 8;
            const float be = dk[2][2 * hh], al = dk[2][2 * hh + 1];
            const uint32_t aa = pack_bf16(al, al);
            const uint32_t w0 = pack_bf16(b, a), w1 = pack_bf16(c, b), w2 = pack_bf16(d, c), w3 = pack_bf16(an, d);
            sts128(wa, w0, pack_bf16(be, hh == 0 ? p0 : p1), w1, pack_bf16(al, be));
            sts128(wa + 16, w2, aa, w3, aa);
            if (hh == 1 && lane >= 28) {
                sts32(wa - 2048 + 4, w0); sts32(wa - 2048 + 12, w1); sts32(wa - 2048 + 20, w2); sts32(wa - 2048 + 28, w3);
            }
        }
        if (lane == 0) { sts32(kt + KT_WD1 + 14 * 8, pack_bf16(f0, 0.f)); sts32(kt + KT_WD1 + 15 * 8, pack_bf16(dk[0][0], f0)); }
        if (warp == 4) asm volatile("bar.arrive 2, 288;\n" ::: "memory");
#pragma unroll
        for (int hh = 0; hh < 2; ++hh) {
            const int i = g + 8 * hh;
            sts32(kt + KT_WD4 + (2 * i + (q & 1) + 32 * (q >> 1) + 8) * 4, pack_bf16(dk[3][2 * hh + 1], dk[3][2 * hh]));
            sts32(kt + KT_WD4 + 320 + (i + 16 * q + 7) * 4, pack_bf16(dk[4][2 * hh + 1], dk[4][2 * hh]));
        }
        if (last) {
            const uint32_t w512 = pack_bf16(f512, 0.f);
            sts32(kt + KT_WD4 + 7 * 4, w512);
            sts128(kt + KT_WD1 + 274 * 8, w512, 0u, w512, 0u);
            sts32(kt + KT_FIX, pack_bf16(f1024, f1024));
        }
    }
    STAMP(3);
    if (role) {
        asm volatile("bar.arrive 13, 256;\n" ::: "memory");
    } else {
        asm volatile("bar.sync 2, 288;\n" ::: "memory");
    }
    STAMP(6);

    const uint32_t ktA = sb + OFF_KT + ch * KT_W, ktB = ktA + 4 * KT_W;
    const int mat = lane >> 3, rr = lane & 7;
    const int np = 4 * (g & 1) + (g >> 1);
    uint32_t k4[9][2][2], k8[8][2][2], kf[2];
    const uint32_t o4 = KT_WD4 + (g - q + 7) * 4;
    const uint32_t o8 = KT_WD4 + 320 + (np + 7 - q) * 4;
#define K_LOAD(DST, OFF, KS)                                                                                 \
        { DST[KS][0][0] = lds32(ktA + OFF + (8 * (KS)) * 4); DST[KS][0][1] = lds32(ktA + OFF + (8 * (KS) - 4) * 4); \
          DST[KS][1][0] = lds32(ktB + OFF + (8 * (KS)) * 4); DST[KS][1][1] = lds32(ktB + OFF + (8 * (KS) - 4) * 4); }
    {
        const int rb = ch >> 1, br = ch & 1;
        const int urole = __shfl_sync(0xffffffffu, role, 0);
        uint32_t wa = sb + OFF_KT + (br * 4 + role) * KT_W + KT_WD1 + (14 + 8 * rb + g - 2 * q) * 8;
        uint2 af[17][2];
#define A_LOAD(S)                                                                                            \
        if ((S) < 16) { af[S][0] = lds64(wa + 128 * (S)); af[S][1] = lds64(wa + 128 * (S) - 64); }           \
        else { af[S][0] = make_uint2(0u, lds32(wa + 128 * (S) + 4)); af[S][1] = make_uint2(0u, lds32(wa + 128 * (S) - 60)); }
        if (urole) asm volatile("bar.sync 9, 384;\n" ::: "memory");
#pragma unroll
        for (int s = 0; s < 9; ++s) { A_LOAD(s) }
#pragma unroll 1
        for (int cc = 0; cc < 2; ++cc) {
#pragma unroll
            for (int s = 9; s < 17; ++s) { A_LOAD(s) }
            const int c = urole + 2 * cc;
            const uint32_t desc = (((sb + OFF_V + c * V_CH + 256) & 0x3FFFFu) >> 4) | ((V_H >> 4) << 16);
            float d[64];
            if (urole | cc) asm volatile("bar.sync %0, 256;\n" :: "r"(5 + urole) : "memory");
            else asm volatile("bar.arrive 9, 384;\n" ::: "memory");
            asm volatile("wgmma.fence.sync.aligned;\n" ::: "memory");
#pragma unroll
            for (int s = 0; s < 9; ++s) wgmma_n128(d, af[s][0].x, af[s][0].y, af[s][1].x, af[s][1].y, desc - s, s);
            asm volatile("wgmma.commit_group.sync.aligned;\n" ::: "memory");
#pragma unroll
            for (int s = 9; s < 17; ++s)
                wgmma_n128(d, af[s][0].x, af[s][0].y, af[s][1].x, af[s][1].y, desc - s, 1);
            asm volatile("wgmma.commit_group.sync.aligned;\n" ::: "memory");
            if (!(urole & cc)) asm volatile("bar.arrive %0, 256;\n" :: "r"(6 - urole) : "memory");
            if (!(urole | cc)) asm volatile("bar.sync 13, 256;\n" ::: "memory");
            asm volatile("wgmma.wait_group.sync.aligned 1;\n" ::: "memory");
            wa += 2 * KT_W;
            if (cc == 0) {
#pragma unroll
                for (int s = 0; s < 9; ++s) { A_LOAD(s) }
            }
            asm volatile("wgmma.wait_group.sync.aligned 0;\n" ::: "memory");
#pragma unroll
            for (int i = 0; i < 64; ++i) asm volatile("" : "+f"(d[i]) :: "memory");
            if (urole & cc) asm volatile("bar.arrive 7, 256;\n" ::: "memory");
            if (cc == 0) STAMP(4); else STAMP(5);
            if (rb == 1 && (lane | 4) == 31) {
                const uint32_t u01 = lds32(sb + OFF_V + c * V_CH + 256);
                const float f512 = bf_lo(lds32(wa - 2 * KT_W + 252 * 8));
                d[13] = fmaf(f512, lane == 27 ? bf_lo(u01) : bf_lo(u01) + bf_hi(u01), d[13]);
            }
            const uint32_t dst = sb + OFF_S1P + c * 8192 + br * 4096 + (32 * q + g) * 4;
#pragma unroll
            for (int j = 0; j < 16; j += 2)
#pragma unroll
                for (int e = 0; e < 2; ++e) {
                    const float y0 = j >= 2 ? d[4 * j + e] + d[4 * j - 6 + e] : d[4 * j + e];
                    const float y1 = j >= 2 ? d[4 * j + 4 + e] + d[4 * j - 2 + e] : d[4 * j + 4 + e];
                    sts32(dst + j * 256 + ((16 * e + 8 * rb) ^ (8 * q)) * 4, pack_bf16(y0, y1));
                }
            __syncwarp();
            if (lane == 0) mbar_arrive(sb + OFF_MB_P);
        }
#undef A_LOAD
    }
    STAMP(7);

    {
        const uint32_t s2 = sb + OFF_SG2 + ch * SG2_CH;
        const uint32_t b4 = s2 + ((rr & 1) ? G2_W3 : G2_W5) + (18 + 9 * (mat & 1) + 4 * (mat >> 1) + (rr >> 1)) * 16;
        const int d8 = 6 + 8 * (mat >> 1) + rr + (mat & 1);
        const uint32_t b8 = s2 + ((rr & 1) ? ((d8 & 1) ? G2_W7O : G2_W7E) : ((d8 & 1) ? G2_W9O : G2_W9E)) + (d8 >> 1) * 16;
        const uint32_t bf = s2 + ((mat & 1) ? G2_P2O : G2_P2E) + rr * 16;
        const uint32_t pg = sb + OFF_PG2 + ch * 6144 + (32 * (q >> 1) + g) * 4;
        const int blk = 2 + role;
        const uint32_t c8 = b8 + (4 * blk - 8) * 128, c4 = b4 + (8 * blk - 8) * 144;
#define G2_STORE(ACC, BLK)                                                                                   \
        _Pragma("unroll") for (int tj = 0; tj < 4; tj += 2)                                                  \
            _Pragma("unroll") for (int br = 0; br < 2; ++br)                                                 \
                _Pragma("unroll") for (int c = 0; c < 4; ++c)                                                \
                    sts32(pg + br * 3072 + ((BLK) - 1) * 1024 + tj * 256 + (c >> 1) * 256 +                  \
                          (16 * ((q & 1) ^ (c >> 1)) + 8 * ((c & 1) ^ (q >> 1))) * 4,                        \
                          pack_bf16(ACC[tj][br][c], ACC[tj + 1][br][c]));                                    \
        __syncwarp();                                                                                         \
        if (lane == 0) mbar_arrive(sb + OFF_MB_P + 8 * (BLK));
        uint32_t fa[4], fb[4], fc[4], fd[4], fx[4][2];
#pragma unroll
        for (int ks = 0; ks < 9; ++ks) K_LOAD(k4, o4, ks);
        {
            const uint32_t msk = ((np >> 1) == q) ? ((np & 1) ? 0xFFFF0000u : 0x0000FFFFu) : 0u;
            kf[0] = lds32(ktA + KT_FIX) & msk; kf[1] = lds32(ktB + KT_FIX) & msk;
        }
#pragma unroll
        for (int ks = 0; ks < 4; ++ks) K_LOAD(k8, o8, ks);
        if (role) {
#pragma unroll
            for (int ks = 4; ks < 8; ++ks) K_LOAD(k8, o8, ks);
        }
        asm volatile("bar.sync %0, 256;\n" :: "r"(3 + role) : "memory");
        STAMP(8);
        float a8[4][2][4];
#pragma unroll
        for (int tj = 0; tj < 4; ++tj)
#pragma unroll
            for (int br = 0; br < 2; ++br) { a8[tj][br][0] = a8[tj][br][1] = a8[tj][br][2] = a8[tj][br][3] = 0.f; }
        if (role == 0) {
            ldsm4t(fa, b4 - 2 * 144); ldsm4t(fb, b4 - 144);
            asm volatile("bar.sync 7, 256;\n" ::: "memory");
            float a1[4][2][4];
#pragma unroll
            for (int tj = 0; tj < 4; ++tj)
#pragma unroll
                for (int br = 0; br < 2; ++br) { a1[tj][br][0] = a1[tj][br][1] = a1[tj][br][2] = a1[tj][br][3] = 0.f; }
            toep_block<2, 8, -2, 6, 144>(a1, k4, b4, fa, fb);
            G2_STORE(a1, 1);
            STAMP(9);
        } else {
            ldsm4t(fc, b8); ldsm4t(fd, b8 + 128);
            toep_block<1, 7, -4, -1, 128>(a8, k8, b8 + 4 * 128, fc, fd);
        }
#pragma unroll
        for (int tj = 0; tj < 4; ++tj) ldsm2t(fx[tj][0], fx[tj][1], bf + (4 * blk - 8 + tj) * 128);
        ldsm4t(fc, c8); ldsm4t(fd, c8 + 128);
        ldsm4t(fa, c4 - 8 * 144); ldsm4t(fb, c4 - 7 * 144);
#pragma unroll
        for (int tj = 0; tj < 4; ++tj) { mma_bf16_k8(a8[tj][0], fx[tj][0], fx[tj][1], kf[0]); mma_bf16_k8(a8[tj][1], fx[tj][0], fx[tj][1], kf[1]); }
        toep_block<1, 7, 0, 3, 128>(a8, k8, c8, fc, fd);
        float a4[4][2][4];
#pragma unroll
        for (int tj = 0; tj < 4; ++tj)
#pragma unroll
            for (int br = 0; br < 2; ++br) {
                a4[tj][br][0] = a8[tj][br][0]; a4[tj][br][1] = a8[tj][br][2];
                a4[tj][br][2] = a8[tj][br][1]; a4[tj][br][3] = a8[tj][br][3];
            }
        toep_block<2, 8, -8, 6, 144>(a4, k4, c4, fa, fb);
        G2_STORE(a4, blk);
        STAMP(10);
#undef G2_STORE
#undef K_LOAD
    }
    asm volatile("barrier.cluster.wait.acquire.aligned;\n" ::: "memory");
    if (role == 0) {
        asm volatile("bar.sync 10, 256;\n" ::: "memory");
        mbar_wait(sb + OFF_MB_P);
        final_block(&tm_out, sb, cl, rank, tid, 2, 11);
        STAMP(11);
        if (tid == 0) asm volatile("cp.async.bulk.wait_group.read 0;\n" ::: "memory");
    }
}

typedef CUresult (*EncodeFn)(CUtensorMap*, CUtensorMapDataType, cuuint32_t, void*, const cuuint64_t*, const cuuint64_t*,
                             const cuuint32_t*, const cuuint32_t*, CUtensorMapInterleave, CUtensorMapSwizzle,
                             CUtensorMapL2promotion, CUtensorMapFloatOOBfill);

}

extern "C" void kernel_launch(void* const* d_in, const int* in_sizes, int n_in, void* d_out, int out_size) {
    (void)in_sizes; (void)n_in; (void)out_size;
    static EncodeFn encode = nullptr;
    if (!encode) {
        void* fn = nullptr;
        cudaDriverEntryPointQueryResult qr;
        cudaGetDriverEntryPoint("cuTensorMapEncodeTiled", &fn, cudaEnableDefault, &qr);
        encode = (EncodeFn)fn;
        cudaFuncSetAttribute(fused_s4d_kernel, cudaFuncAttributeMaxDynamicSharedMemorySize, SMEM_BYTES);
    }
    CUtensorMap tin, tout;
    {
        cuuint64_t gd[3] = {DCH, 128, 16};
        cuuint64_t gs[2] = {16 * 1024, 1024};
        cuuint32_t bx[3] = {8, 128, 8};
        cuuint32_t es[3] = {1, 1, 1};
        encode(&tin, CU_TENSOR_MAP_DATA_TYPE_BFLOAT16, 3, d_in[0], gd, gs, bx, es, CU_TENSOR_MAP_INTERLEAVE_NONE,
               CU_TENSOR_MAP_SWIZZLE_NONE, CU_TENSOR_MAP_L2_PROMOTION_NONE, CU_TENSOR_MAP_FLOAT_OOB_FILL_NONE);
    }
    {
        cuuint64_t gd[4] = {DCH, 128, 2, 8};
        cuuint64_t gs[3] = {2048, 1024, 256 * 1024};
        cuuint32_t bx[4] = {8, 64, 2, 2};
        cuuint32_t es[4] = {1, 1, 1, 1};
        encode(&tout, CU_TENSOR_MAP_DATA_TYPE_BFLOAT16, 4, d_out, gd, gs, bx, es, CU_TENSOR_MAP_INTERLEAVE_NONE,
               CU_TENSOR_MAP_SWIZZLE_NONE, CU_TENSOR_MAP_L2_PROMOTION_NONE, CU_TENSOR_MAP_FLOAT_OOB_FILL_NONE);
    }
    Params prm;
    prm.u = (const __nv_bfloat16*)d_in[0];
    for (int j = 0; j < 6; ++j) {
        prm.p[0][j] = (const __nv_bfloat16*)d_in[1 + j];
        prm.p[1][j] = (const __nv_bfloat16*)d_in[8 + j];
    }
    prm.gw = (const __nv_bfloat16*)d_in[14];
    fused_s4d_kernel<<<128, NTHREADS, SMEM_BYTES, cudaStreamPerThread>>>(prm, tin, tout);
}
```

```cpp
#include <cuda_runtime.h>
#include <cuda_bf16.h>
#include <cuda_fp16.h>
#include <cuda.h>
#include <stdint.h>

#define PROFILE_CLK 0

namespace {

constexpr int LSEQ = 2048;
constexpr int DCH = 512;
constexpr int NTHREADS = 384;

constexpr int OFF_U = 0;
constexpr int OFF_ROWS = OFF_U;
constexpr int G2_W5 = 0, G2_W3 = 3776, G2_W9E = 7552, G2_W9O = G2_W9E + 1152, G2_W7E = G2_W9O + 1152 + 48,
              G2_W7O = G2_W7E + 1152 + 16, G2_P2E = G2_W7O + 1088 + 64, G2_P2O = G2_P2E + 1024, SG2_CH = 14336;
static_assert((G2_W7O - G2_W9E) % 128 == 64 && (G2_W7E + 16 - G2_W9O) % 128 == 64 && G2_P2O + 1024 <= SG2_CH, "banks");
constexpr int OFF_SG2 = 32768;
constexpr int V_H = 144 * 16, V_CH = 2 * V_H;
constexpr int OFF_V = OFF_SG2 + 4 * SG2_CH;
constexpr int OFF_S1P = OFF_V + 4 * V_CH;
constexpr int OFF_PG2 = OFF_S1P + 32768;
constexpr int OFF_GT = OFF_PG2 + 24576;
constexpr int FT_W = 8 * 71 * 16;
constexpr int OFF_FT = OFF_S1P;
constexpr int KT_W = 2960;
constexpr int KT_WD1 = 0, KT_WD4 = 288 * 8, KT_FIX = KT_WD4 + 2 * 320;
constexpr int OFF_KT = OFF_FT + 8 * FT_W;
constexpr int OFF_OUT = OFF_KT + 8 * KT_W;
constexpr int OFF_MISC = OFF_OUT + 8192;
constexpr int OFF_MB_U = OFF_MISC, OFF_MB_P = OFF_MISC + 8, OFF_MB_OUT = OFF_MISC + 40;
constexpr int OFF_TAG = OFF_MISC + 72;
constexpr int OFF_GPART = OFF_MISC + 128;
constexpr int SMEM_BYTES = OFF_GPART + 256;
static_assert(OFF_V % 128 == 0 && OFF_S1P % 128 == 0 && OFF_KT % 128 == 0 && OFF_OUT % 128 == 0, "align");
static_assert(OFF_GT + 8192 <= OFF_KT && KT_FIX + 4 <= KT_W && SMEM_BYTES <= 232448, "smem");

struct Params {
    const __nv_bfloat16* u;
    const __nv_bfloat16* p[2][6];
    const __nv_bfloat16* gw;
};

__device__ __align__(128) uint32_t g_gate[LSEQ];
__device__ uint32_t g_count;
#define STAMP(i) do {} while (0)
#define GSTAMP(i) do {} while (0)

__device__ __forceinline__ void ldsm4(uint32_t (&r)[4], uint32_t a) {
    asm volatile("ldmatrix.sync.aligned.m8n8.x4.shared.b16 {%0,%1,%2,%3},[%4];\n"
                 : "=r"(r[0]), "=r"(r[1]), "=r"(r[2]), "=r"(r[3]) : "r"(a) : "memory");
}
__device__ __forceinline__ void ldsm4t(uint32_t (&r)[4], uint32_t a) {
    asm volatile("ldmatrix.sync.aligned.m8n8.x4.trans.shared.b16 {%0,%1,%2,%3},[%4];\n"
                 : "=r"(r[0]), "=r"(r[1]), "=r"(r[2]), "=r"(r[3]) : "r"(a) : "memory");
}
__device__ __forceinline__ void ldsm2t(uint32_t& r0, uint32_t& r1, uint32_t a) {
    asm volatile("ldmatrix.sync.aligned.m8n8.x2.trans.shared.b16 {%0,%1},[%2];\n" : "=r"(r0), "=r"(r1) : "r"(a) : "memory");
}
__device__ __forceinline__ void mma_bf16(float (&d)[4], const uint32_t (&a)[4], uint32_t b0, uint32_t b1) {
    asm("mma.sync.aligned.m16n8k16.row.col.f32.bf16.bf16.f32 {%0,%1,%2,%3},{%4,%5,%6,%7},{%8,%9},{%0,%1,%2,%3};\n"
        : "+f"(d[0]), "+f"(d[1]), "+f"(d[2]), "+f"(d[3])
        : "r"(a[0]), "r"(a[1]), "r"(a[2]), "r"(a[3]), "r"(b0), "r"(b1));
}
__device__ __forceinline__ void mma_bf16_k8(float (&d)[4], uint32_t a0, uint32_t a1, uint32_t b0) {
    asm("mma.sync.aligned.m16n8k8.row.col.f32.bf16.bf16.f32 {%0,%1,%2,%3},{%4,%5},{%6},{%0,%1,%2,%3};\n"
        : "+f"(d[0]), "+f"(d[1]), "+f"(d[2]), "+f"(d[3]) : "r"(a0), "r"(a1), "r"(b0));
}
__device__ __forceinline__ void mma_f16(float (&d)[4], const uint32_t (&a)[4], uint32_t b0, uint32_t b1) {
    asm("mma.sync.aligned.m16n8k16.row.col.f32.f16.f16.f32 {%0,%1,%2,%3},{%4,%5,%6,%7},{%8,%9},{%0,%1,%2,%3};\n"
        : "+f"(d[0]), "+f"(d[1]), "+f"(d[2]), "+f"(d[3])
        : "r"(a[0]), "r"(a[1]), "r"(a[2]), "r"(a[3]), "r"(b0), "r"(b1));
}
__device__ __forceinline__ uint32_t lds32(uint32_t a) {
    uint32_t v; asm volatile("ld.shared.u32 %0,[%1];\n" : "=r"(v) : "r"(a) : "memory"); return v;
}
__device__ __forceinline__ uint4 lds128(uint32_t a) {
    uint4 v; asm volatile("ld.shared.v4.u32 {%0,%1,%2,%3},[%4];\n" : "=r"(v.x), "=r"(v.y), "=r"(v.z), "=r"(v.w) : "r"(a) : "memory");
    return v;
}
__device__ __forceinline__ void sts32(uint32_t a, uint32_t v) { asm volatile("st.shared.u32 [%0],%1;\n" :: "r"(a), "r"(v) : "memory"); }
__device__ __forceinline__ void sts128(uint32_t a, uint32_t x, uint32_t y, uint32_t z, uint32_t w) {
    asm volatile("st.shared.v4.u32 [%0],{%1,%2,%3,%4};\n" :: "r"(a), "r"(x), "r"(y), "r"(z), "r"(w) : "memory");
}
__device__ __forceinline__ uint32_t pack_bf16(float lo, float hi) {
    uint32_t r; asm("cvt.rn.bf16x2.f32 %0,%1,%2;\n" : "=r"(r) : "f"(hi), "f"(lo)); return r;
}
__device__ __forceinline__ uint32_t pack_f16(float lo, float hi) {
    uint32_t r; asm("cvt.rn.f16x2.f32 %0,%1,%2;\n" : "=r"(r) : "f"(hi), "f"(lo)); return r;
}
__device__ __forceinline__ uint32_t badd2(uint32_t a, uint32_t b) {
    uint32_t r; asm("add.rn.bf16x2 %0,%1,%2;\n" : "=r"(r) : "r"(a), "r"(b)); return r;
}
__device__ __forceinline__ uint32_t bmul2(uint32_t a, uint32_t b) {
    uint32_t r; asm("mul.rn.bf16x2 %0,%1,%2;\n" : "=r"(r) : "r"(a), "r"(b)); return r;
}
__device__ __forceinline__ void sts64(uint32_t a, uint32_t x, uint32_t y) {
    asm volatile("st.shared.v2.u32 [%0],{%1,%2};\n" :: "r"(a), "r"(x), "r"(y) : "memory");
}
__device__ __forceinline__ uint2 lds64(uint32_t a) {
    uint2 v; asm volatile("ld.shared.v2.u32 {%0,%1},[%2];\n" : "=r"(v.x), "=r"(v.y) : "r"(a) : "memory"); return v;
}
__device__ __forceinline__ uint32_t bfma2(uint32_t a, uint32_t b, uint32_t c) {
    uint32_t r; asm("fma.rn.bf16x2 %0,%1,%2,%3;\n" : "=r"(r) : "r"(a), "r"(b), "r"(c)); return r;
}
__device__ __forceinline__ uint32_t plo(uint32_t a, uint32_t b) { return __byte_perm(a, b, 0x5410); }
__device__ __forceinline__ uint32_t phi(uint32_t a, uint32_t b) { return __byte_perm(a, b, 0x7632); }
__device__ __forceinline__ float bf_lo(uint32_t v) { return __uint_as_float(v << 16); }
__device__ __forceinline__ float bf_hi(uint32_t v) { return __uint_as_float(v & 0xFFFF0000u); }
__device__ __forceinline__ float bf_round(float x) { return __bfloat162float(__float2bfloat16_rn(x)); }

__device__ __forceinline__ void mbar_init(uint32_t a, uint32_t cnt) {
    asm volatile("mbarrier.init.shared.b64 [%0],%1;\n" :: "r"(a), "r"(cnt) : "memory");
}
__device__ __forceinline__ void mbar_arrive(uint32_t a) {
    asm volatile("mbarrier.arrive.shared.b64 _,[%0];\n" :: "r"(a) : "memory");
}
__device__ __forceinline__ void mbar_expect(uint32_t a, uint32_t bytes) {
    asm volatile("mbarrier.arrive.expect_tx.shared.b64 _,[%0],%1;\n" :: "r"(a), "r"(bytes) : "memory");
}
__device__ __forceinline__ void mbar_wait(uint32_t a) {
    uint32_t ok = 0;
#pragma unroll 1
    for (int it = 0; it < (1 << 20) && !ok; ++it)
        asm volatile("{.reg .pred p; mbarrier.try_wait.parity.shared.b64 p,[%1],0; selp.u32 %0,1,0,p;}\n"
                     : "=r"(ok) : "r"(a) : "memory");
}
__device__ __forceinline__ void mbar_wait_cluster(uint32_t a) {
    uint32_t ok = 0;
#pragma unroll 1
    for (int it = 0; it < (1 << 20) && !ok; ++it)
        asm volatile("{.reg .pred p; mbarrier.try_wait.parity.acquire.cluster.shared.b64 p,[%1],0; selp.u32 %0,1,0,p;}\n"
                     : "=r"(ok) : "r"(a) : "memory");
}

struct c32 { float x, y; };
__device__ __forceinline__ c32 csq(c32 z) { c32 r; r.x = fmaf(z.x, z.x, -(z.y * z.y)); r.y = (z.x + z.x) * z.y; return r; }
__device__ __forceinline__ c32 cexp_seed(float al2, float ai, float x) {
    float m, s, c, th = ai * x, e = al2 * x;
    asm("ex2.approx.ftz.f32 %0,%1;\n" : "=f"(m) : "f"(e));
    asm("sin.approx.ftz.f32 %0,%1;\n" : "=f"(s) : "f"(th));
    asm("cos.approx.ftz.f32 %0,%1;\n" : "=f"(c) : "f"(th));
    c32 r; r.x = m * c; r.y = m * s; return r;
}
typedef unsigned long long pc;
__device__ __forceinline__ pc mk64(uint32_t re, uint32_t im) { pc r; asm("mov.b64 %0,{%1,%2};\n" : "=l"(r) : "r"(re), "r"(im)); return r; }
__device__ __forceinline__ pc mkp(c32 a, c32 b) {
    pc r;
    asm("{.reg .b32 x,y; cvt.rn.f16x2.f32 x,%2,%1; cvt.rn.f16x2.f32 y,%4,%3; mov.b64 %0,{x,y};}\n"
        : "=l"(r) : "f"(a.x), "f"(b.x), "f"(a.y), "f"(b.y));
    return r;
}
__device__ __forceinline__ pc pmul(pc z, pc w) {
    pc r;
    asm("{.reg .b32 zr,zi,wr,wi,t0,t1,n; mov.b64 {zr,zi},%1; mov.b64 {wr,wi},%2;\n"
        "mul.rn.f16x2 t0,zr,wr; mul.rn.f16x2 t1,zi,wr; neg.f16x2 n,zi;\n"
        "fma.rn.f16x2 t0,n,wi,t0; fma.rn.f16x2 t1,zr,wi,t1; mov.b64 %0,{t0,t1};}\n"
        : "=l"(r) : "l"(z), "l"(w));
    return r;
}
__device__ __forceinline__ void stp(uint32_t a, pc v) {
    asm volatile("{.reg .b32 x,y; mov.b64 {x,y},%1; stmatrix.sync.aligned.m8n8.x2.shared.b16 [%0],{x,y};}\n"
                 :: "r"(a), "l"(v) : "memory");
}
__device__ __forceinline__ void mma_f16p(float (&d)[4], const uint32_t (&a)[4], pc b) {
    asm("{.reg .b32 x,y; mov.b64 {x,y},%8;\n"
        "mma.sync.aligned.m16n8k16.row.col.f32.f16.f16.f32 {%0,%1,%2,%3},{%4,%5,%6,%7},{x,y},{%0,%1,%2,%3};}\n"
        : "+f"(d[0]), "+f"(d[1]), "+f"(d[2]), "+f"(d[3]) : "r"(a[0]), "r"(a[1]), "r"(a[2]), "r"(a[3]), "l"(b));
}

__device__ __forceinline__ void store_pair(uint32_t a0, uint32_t a1, uint32_t v0, uint32_t v1, uint32_t v2, uint32_t v3,
                                           uint32_t v4, uint32_t v5, uint32_t v6, uint32_t v7) {
    sts128(a0, plo(v0, v1), plo(v2, v3), plo(v4, v5), plo(v6, v7));
    sts128(a1, phi(v0, v1), phi(v2, v3), phi(v4, v5), phi(v6, v7));
}

__device__ __forceinline__ void wgmma_n128(float (&d)[64], uint32_t a0, uint32_t a1, uint32_t a2, uint32_t a3, uint32_t dlo,
                                           int accumulate) {
    asm volatile("{.reg .pred p; .reg .b64 ds; setp.ne.s32 p,%69,0; mov.b64 ds,{%68,%70};\n"
                 "wgmma.mma_async.sync.aligned.m64n128k16.f32.bf16.bf16 {%0,%1,%2,%3,%4,%5,%6,%7,%8,%9,%10,%11,%12,%13,%14,%15,%16,%17,%18,%19,%20,%21,%22,%23,%24,%25,%26,%27,%28,%29,%30,%31,%32,%33,%34,%35,%36,%37,%38,%39,%40,%41,%42,%43,%44,%45,%46,%47,%48,%49,%50,%51,%52,%53,%54,%55,%56,%57,%58,%59,%60,%61,%62,%63},\n"
                 "{%64,%65,%66,%67},ds,p,1,1,0;}\n"
                 : "+f"(d[0]),"+f"(d[1]),"+f"(d[2]),"+f"(d[3]),"+f"(d[4]),"+f"(d[5]),"+f"(d[6]),"+f"(d[7]),"+f"(d[8]),"+f"(d[9]),"+f"(d[10]),"+f"(d[11]),"+f"(d[12]),"+f"(d[13]),"+f"(d[14]),"+f"(d[15]),"+f"(d[16]),"+f"(d[17]),"+f"(d[18]),"+f"(d[19]),"+f"(d[20]),"+f"(d[21]),"+f"(d[22]),"+f"(d[23]),"+f"(d[24]),"+f"(d[25]),"+f"(d[26]),"+f"(d[27]),"+f"(d[28]),"+f"(d[29]),"+f"(d[30]),"+f"(d[31]),"+f"(d[32]),"+f"(d[33]),"+f"(d[34]),"+f"(d[35]),"+f"(d[36]),"+f"(d[37]),"+f"(d[38]),"+f"(d[39]),"+f"(d[40]),"+f"(d[41]),"+f"(d[42]),"+f"(d[43]),"+f"(d[44]),"+f"(d[45]),"+f"(d[46]),"+f"(d[47]),"+f"(d[48]),"+f"(d[49]),"+f"(d[50]),"+f"(d[51]),"+f"(d[52]),"+f"(d[53]),"+f"(d[54]),"+f"(d[55]),"+f"(d[56]),"+f"(d[57]),"+f"(d[58]),"+f"(d[59]),"+f"(d[60]),"+f"(d[61]),"+f"(d[62]),"+f"(d[63])
                 : "r"(a0), "r"(a1), "r"(a2), "r"(a3), "r"(dlo), "r"(accumulate), "n"(128 >> 4));
}

template <int TS, int KMAX, int LO, int HI, int STRIDE>
__device__ __forceinline__ void toep_block(float (&acc)[4][2][4], const uint32_t (&kb)[KMAX + 1][2][2], uint32_t base,
                                           const uint32_t (&f0)[4], const uint32_t (&f1)[4]) {
    uint32_t fr[4][4];
#pragma unroll
    for (int j = 0; j < 4; ++j) { fr[0][j] = f0[j]; fr[1][j] = f1[j]; }
    if (LO + 2 <= HI) ldsm4t(fr[2], base + (uint32_t)((LO + 2) * STRIDE));
#pragma unroll
    for (int loc = LO; loc <= HI; ++loc) {
        if (loc + 3 <= HI) ldsm4t(fr[(loc + 3 - LO) & 3], base + (loc + 3) * STRIDE);
#pragma unroll
        for (int tj = 0; tj < 4; ++tj) {
            const int ks = TS * tj - loc;
            if (ks >= 0 && ks <= KMAX) {
                mma_bf16(acc[tj][0], fr[(loc - LO) & 3], kb[ks][0][0], kb[ks][0][1]);
                mma_bf16(acc[tj][1], fr[(loc - LO) & 3], kb[ks][1][0], kb[ks][1][1]);
            }
        }
    }
}

__device__ __forceinline__ uint32_t gate_word(float s) {
    float sb = bf_round(s);
    float g = bf_round(1.0f / (1.0f + expf(-sb)));
    float o = bf_round(1.0f - g);
    return ((__float_as_uint(g) >> 16) | (__float_as_uint(o) & 0xFFFF0000u)) & 0x7FFF7FFFu;
}

__device__ __forceinline__ void final_block(const CUtensorMap* tm, uint32_t sb, int cl, int rank, int un, int b, int barid) {
    uint32_t oaddr, obar;
    asm("mapa.shared::cluster.u32 %0,%1,%2;\n" : "=r"(oaddr) : "r"(sb + OFF_OUT + b * 2048 + un * 16), "r"(rank ^ 1));
    asm("mapa.shared::cluster.u32 %0,%1,%2;\n" : "=r"(obar) : "r"(sb + OFF_MB_OUT + 8 * b), "r"(rank ^ 1));
    const uint32_t orow = sb + OFF_ROWS + b * 4096 + (un >> 6) * 2048 + (un & 63) * 16;
    const uint32_t sw = ((2 * un) ^ ((un >> 1) & 0x18)) * 4 + b * 1024;
    const uint32_t psel = rank ? 0x7632u : 0x5410u;
    uint2 ya[4], yb[4];
    const uint4 gw = lds128(sb + OFF_GT + (b * 256 + 2 * un) * 8);
#pragma unroll
    for (int c = 0; c < 4; ++c) {
        ya[c] = lds64(sb + OFF_S1P + c * 8192 + sw);
        yb[c] = lds64(sb + OFF_S1P + c * 8192 + 4096 + sw);
    }
    if (b > 0) {
        mbar_wait(sb + OFF_MB_P + 8 * b);
#pragma unroll
        for (int c = 0; c < 4; ++c) {
            const uint2 za = lds64(sb + OFF_PG2 - 1024 + c * 6144 + sw);
            const uint2 zb = lds64(sb + OFF_PG2 - 1024 + c * 6144 + 3072 + sw);
            ya[c].x = badd2(ya[c].x, za.x); ya[c].y = badd2(ya[c].y, za.y);
            yb[c].x = badd2(yb[c].x, zb.x); yb[c].y = badd2(yb[c].y, zb.y);
        }
    }
    uint32_t o0[4], o1[4];
#pragma unroll
    for (int c = 0; c < 4; ++c) {
        o0[c] = bfma2(ya[c].x, gw.x, bmul2(yb[c].x, gw.y));
        o1[c] = bfma2(ya[c].y, gw.z, bmul2(yb[c].y, gw.w));
    }
    asm volatile("st.async.weak.shared::cluster.mbarrier::complete_tx::bytes.v4.b32 [%0],{%1,%2,%3,%4},[%5];\n"
                 :: "r"(oaddr), "r"(__byte_perm(o0[0], o0[1], psel ^ 0x2222u)), "r"(__byte_perm(o0[2], o0[3], psel ^ 0x2222u)),
                    "r"(__byte_perm(o1[0], o1[1], psel ^ 0x2222u)), "r"(__byte_perm(o1[2], o1[3], psel ^ 0x2222u)),
                    "r"(obar) : "memory");
    sts64(orow + rank * 8, __byte_perm(o0[0], o0[1], psel), __byte_perm(o0[2], o0[3], psel));
    sts64(orow + 1024 + rank * 8, __byte_perm(o1[0], o1[1], psel), __byte_perm(o1[2], o1[3], psel));
    mbar_wait_cluster(sb + OFF_MB_OUT + 8 * b);
    const uint4 pe = lds128(sb + OFF_OUT + b * 2048 + un * 16);
    sts64(orow + 8 - rank * 8, pe.x, pe.y);
    sts64(orow + 1032 - rank * 8, pe.z, pe.w);
    asm volatile("fence.proxy.async.shared::cta;\n" ::: "memory");
    asm volatile("bar.sync %0, 128;\n" :: "r"(barid) : "memory");
    if (un == 0) {
        asm volatile("cp.async.bulk.tensor.4d.global.shared::cta.bulk_group [%0,{%1,%2,%3,%4}],[%5];\n"
                     :: "l"(tm), "r"(8 * cl), "r"(64 * rank), "r"(0), "r"(2 * b), "r"(sb + OFF_ROWS + b * 4096) : "memory");
        asm volatile("cp.async.bulk.commit_group;\n" ::: "memory");
    }
}

__global__ void __cluster_dims__(2, 1, 1) __launch_bounds__(NTHREADS, 1)
fused_s4d_kernel(const __grid_constant__ Params prm, const __grid_constant__ CUtensorMap tm_in,
                 const __grid_constant__ CUtensorMap tm_out) {
    extern __shared__ __align__(1024) unsigned char smem[];
    const uint32_t sb = (uint32_t)__cvta_generic_to_shared(smem);
    const int tid = threadIdx.x, warp = tid >> 5, lane = tid & 31;
    const int rank = blockIdx.x & 1, cl = blockIdx.x >> 1;
    if (warp != 8) asm volatile("barrier.cluster.arrive.relaxed.aligned;\n" ::: "memory");
    STAMP(0);
    if (tid == 128) GSTAMP(0);

    if (warp >= 8) {
        const int un = tid - 256;
        if (warp == 8) {
            if (lane == 0) {
                asm volatile("prefetch.tensormap [%0];\n" :: "l"(&tm_in) : "memory");
                asm volatile("prefetch.tensormap [%0];\n" :: "l"(&tm_out) : "memory");
                mbar_init(sb + OFF_MB_U, 1);
                mbar_init(sb + OFF_MB_P, 16);
#pragma unroll
                for (int i = 1; i < 4; ++i) mbar_init(sb + OFF_MB_P + 8 * i, 4);
#pragma unroll
                for (int i = 0; i < 4; ++i) mbar_init(sb + OFF_MB_OUT + 8 * i, 1);
                mbar_expect(sb + OFF_MB_U, 32768);
#pragma unroll
                for (int i = 0; i < 4; ++i) mbar_expect(sb + OFF_MB_OUT + 8 * i, 2048);
                asm volatile("fence.mbarrier_init.release.cluster;\n" ::: "memory");
                asm volatile("fence.proxy.async.shared::cta;\n" ::: "memory");
            }
            __syncwarp();
            asm volatile("barrier.cluster.arrive.relaxed.aligned;\n" ::: "memory");
        }
        asm volatile("barrier.cluster.wait.acquire.aligned;\n" ::: "memory");
        if (un == 0) {
            asm volatile("cp.async.bulk.tensor.3d.shared::cluster.global.mbarrier::complete_tx::bytes.multicast::cluster "
                         "[%0],[%1,{%2,%3,%4}],[%5],%6;\n"
                         :: "r"(sb + OFF_U + rank * 16384), "l"(&tm_in), "r"(8 * cl), "r"(0), "r"(8 * rank), "r"(sb + OFF_MB_U),
                            "h"((uint16_t)3) : "memory");
        }
        STAMP(9);
        {
            const uint32_t a2 = sb + OFF_SG2 + (warp - 8) * SG2_CH;
            sts128(a2 + (lane < 16 ? G2_W5 : G2_W3) + ((lane & 15) + ((lane >> 3) & 1)) * 16, 0, 0, 0, 0);
            if (lane < 16) sts128(a2 + (lane < 4 ? G2_W9E : lane < 8 ? G2_W9O : lane < 12 ? G2_W7E : G2_W7O) + (lane & 3) * 16, 0, 0, 0, 0);
            sts128(sb + OFF_V + (warp - 8) * V_CH + (lane >> 4) * V_H + (lane & 15) * 16, 0, 0, 0, 0);
        }
        const int g = lane >> 2, q = lane & 3;
        uint32_t epoch = 0;
        if (warp == 8) asm volatile("ld.relaxed.gpu.global.u32 %0,[%1];\n" : "=r"(epoch) : "l"(&g_count) : "memory");
        uint4 gx[8], gwv[4];
        const uint4* ur = reinterpret_cast<const uint4*>(prm.u) + (size_t)(blockIdx.x * 16 + g) * 64 + (warp - 8) * 16 + q;
        const uint4* wr = reinterpret_cast<const uint4*>(prm.gw) + (warp - 8) * 16 + q;
#pragma unroll
        for (int j = 0; j < 4; ++j) { gx[2 * j] = __ldg(ur + 4 * j); gx[2 * j + 1] = __ldg(ur + 8 * 64 + 4 * j); gwv[j] = __ldg(wr + 4 * j); }
        {
            float gs[4] = {0.f, 0.f, 0.f, 0.f}, gt[4] = {0.f, 0.f, 0.f, 0.f};
#pragma unroll
            for (int j = 0; j < 4; ++j) {
                uint32_t a[4], b[4];
                a[0] = bmul2(gx[2 * j].x, gwv[j].x); a[1] = bmul2(gx[2 * j + 1].x, gwv[j].x);
                a[2] = bmul2(gx[2 * j].y, gwv[j].y); a[3] = bmul2(gx[2 * j + 1].y, gwv[j].y);
                b[0] = bmul2(gx[2 * j].z, gwv[j].z); b[1] = bmul2(gx[2 * j + 1].z, gwv[j].z);
                b[2] = bmul2(gx[2 * j].w, gwv[j].w); b[3] = bmul2(gx[2 * j + 1].w, gwv[j].w);
                mma_bf16(gs, a, 0x3F803F80u, 0x3F803F80u);
                mma_bf16(gt, b, 0x3F803F80u, 0x3F803F80u);
            }
            if (q == 0) {
                sts32(sb + OFF_GPART + ((warp - 8) * 16 + g) * 4, __float_as_uint(gs[0] + gt[0]));
                sts32(sb + OFF_GPART + ((warp - 8) * 16 + g + 8) * 4, __float_as_uint(gs[2] + gt[2]));
            }
            asm volatile("bar.sync 1, 128;\n" ::: "memory");
            if (warp == 8) {
                const uint32_t tg = ((epoch >> 7) + 1u) & 3u;
                if (lane < 16) {
                    float t = 0.f;
#pragma unroll
                    for (int w = 0; w < 4; ++w) t += __uint_as_float(lds32(sb + OFF_GPART + (w * 16 + lane) * 4));
                    const uint32_t wd = gate_word(t) | ((tg & 1u) << 15) | ((tg & 2u) << 30);
                    asm volatile("st.relaxed.gpu.global.u32 [%0],%1;\n" :: "l"(&g_gate[blockIdx.x * 16 + lane]), "r"(wd) : "memory");
                }
                if (lane == 0) {
                    sts32(sb + OFF_TAG, ((tg & 1u) << 15) | ((tg & 2u) << 30));
                    asm volatile("red.relaxed.gpu.global.add.u32 [%0],1;\n" :: "l"(&g_count) : "memory");
                }
            }
        }
        STAMP(10);
        mbar_wait(sb + OFF_MB_U);
        STAMP(2);
        {
            const uint32_t ua = sb + OFF_U + un * 16 + rank * 8;
            uint2 v[16];
#pragma unroll
            for (int j = 0; j < 16; ++j) v[j] = lds64(ua + j * 2048);
            const uint32_t a = sb + OFF_V + (16 + un) * 16;
            store_pair(a, a + V_CH, v[0].x, v[1].x, v[2].x, v[3].x, v[4].x, v[5].x, v[6].x, v[7].x);
            store_pair(a + V_H, a + V_H + V_CH, v[8].x, v[9].x, v[10].x, v[11].x, v[12].x, v[13].x, v[14].x, v[15].x);
            store_pair(a + 2 * V_CH, a + 3 * V_CH, v[0].y, v[1].y, v[2].y, v[3].y, v[4].y, v[5].y, v[6].y, v[7].y);
            store_pair(a + V_H + 2 * V_CH, a + V_H + 3 * V_CH, v[8].y, v[9].y, v[10].y, v[11].y, v[12].y, v[13].y, v[14].y, v[15].y);
        }
        asm volatile("fence.proxy.async.shared::cta;\n" ::: "memory");
        asm volatile("bar.arrive 2, 288;\n" ::: "memory");
        STAMP(3);
        asm volatile("bar.sync 9, 384;\n" ::: "memory");
#pragma unroll 1
        for (int it = 0; it < 3; ++it) {
            if (it == 2) {
                asm volatile("bar.arrive 3, 256;\n" ::: "memory");
                STAMP(4);
            }
            const int rho = it * 32 + lane;
            const uint32_t va = sb + OFF_V + (warp - 8) * V_CH + (16 + rho) * 16;
            const uint4 e0 = lds128(va + V_H - 16), e1 = lds128(va), e2 = lds128(va + V_H), e3 = lds128(va + 16);
            const uint32_t E[13] = {e0.z, e0.w, e1.x, e1.y, e1.z, e1.w, e2.x, e2.y, e2.z, e2.w, e3.x, e3.y, e3.z};
            uint32_t O[12], P2[12], W3[12], P4[11], W5[11];
#pragma unroll
            for (int k = 0; k < 12; ++k) { O[k] = __byte_perm(E[k], E[k + 1], 0x5432); P2[k] = badd2(E[k], O[k]); }
#pragma unroll
            for (int k = 1; k < 12; ++k) W3[k] = badd2(O[k - 1], P2[k]);
#pragma unroll
            for (int k = 0; k < 11; ++k) P4[k] = badd2(P2[k], P2[k + 1]);
#pragma unroll
            for (int k = 2; k < 11; ++k) W5[k] = badd2(P4[k - 1], E[k + 1]);
            const uint32_t s2a = sb + OFF_SG2 + (warp - 8) * SG2_CH;
            const int c5 = 2 * rho + 16;
            const uint32_t a5 = s2a + G2_W5 + (c5 + (c5 >> 3)) * 16, a3 = a5 + (G2_W3 - G2_W5);
            sts128(a5, W5[2], W5[3], W5[4], W5[5]); sts128(a5 + 16, W5[6], W5[7], W5[8], W5[9]);
            sts128(a3, W3[4], W3[5], W3[6], W3[7]); sts128(a3 + 16, W3[8], W3[9], W3[10], W3[11]);
            if (it < 2) {
                uint32_t W7[8], W9[8];
#pragma unroll
                for (int k = 0; k < 8; ++k) { W7[k] = badd2(W3[k + 1], P4[k + 2]); W9[k] = badd2(P4[k], W5[k + 3]); }
                const uint32_t a9 = s2a + (rho + 4) * 16, ap = s2a + rho * 16;
                sts128(a9 + G2_W9E, W9[0], W9[1], W9[2], W9[3]); sts128(a9 + G2_W9O, W9[4], W9[5], W9[6], W9[7]);
                sts128(a9 + G2_W7E, W7[0], W7[1], W7[2], W7[3]); sts128(a9 + G2_W7O, W7[4], W7[5], W7[6], W7[7]);
                sts128(ap + G2_P2E, P2[0], P2[1], P2[2], P2[3]); sts128(ap + G2_P2O, P2[4], P2[5], P2[6], P2[7]);
                if (rho == 0) {
                    const uint32_t n12 = plo(E[2], P2[2]);
                    sts128(a5 - 32, 0, 0, 0, n12);
                    sts128(a3 - 32, 0, W3[1], W3[2], W3[3]);
                    sts128(a9 + G2_W9O - 16, 0, 0, n12, __byte_perm(W3[2], P4[2], 0x5432));
                    sts128(a9 + G2_W7O - 16, 0, 0, E[2] << 16, __byte_perm(P2[2], W3[2], 0x7610));
                }
            }
        }
        asm volatile("bar.arrive 4, 256;\n" ::: "memory");
        {
            const int uc = un;
            const uint32_t tagw = lds32(sb + OFF_TAG);
            bool done = false;
            const int tb0 = (uc >> 5) * 256 + (uc & 31) * 4;
#pragma unroll 1
            for (int tries = 0; tries < 8192 && !done; ++tries) {
                uint4 v[4];
#pragma unroll
                for (int i = 0; i < 4; ++i)
                    asm volatile("ld.relaxed.gpu.global.v4.u32 {%0,%1,%2,%3},[%4];\n"
                                 : "=r"(v[i].x), "=r"(v[i].y), "=r"(v[i].z), "=r"(v[i].w)
                                 : "l"(&g_gate[tb0 + (i >> 1) * 1024 + (i & 1) * 128]) : "memory");
                uint32_t bad = 0;
#pragma unroll
                for (int i = 0; i < 4; ++i)
                    bad |= (v[i].x ^ tagw) | (v[i].y ^ tagw) | (v[i].z ^ tagw) | (v[i].w ^ tagw);
                done = __all_sync(0xffffffffu, (bad & 0x80008000u) == 0);
                if (done) {
#pragma unroll
                    for (int i = 0; i < 2; ++i) {
                        const uint4 a = v[2 * i], b = v[2 * i + 1];
                        const uint32_t d = sb + OFF_GT + (i * 512 + uc * 4) * 8;
                        sts128(d, plo(a.x, b.x) & 0x7FFF7FFFu, phi(a.x, b.x) & 0x7FFF7FFFu, plo(a.y, b.y) & 0x7FFF7FFFu, phi(a.y, b.y) & 0x7FFF7FFFu);
                        sts128(d + 16, plo(a.z, b.z) & 0x7FFF7FFFu, phi(a.z, b.z) & 0x7FFF7FFFu, plo(a.w, b.w) & 0x7FFF7FFFu, phi(a.w, b.w) & 0x7FFF7FFFu);
                    }
                } else {
                    __nanosleep(64);
                }
            }
            if (!done) {
#pragma unroll 1
                for (int k = 0; k < 512; ++k) {
                    const int t = (k >> 8) * 1024 + (uc >> 5) * 256 + (k & 255);
                    float s = 0.f;
#pragma unroll 1
                    for (int j = 0; j < 8; ++j) {
                        const uint32_t pr = bmul2(reinterpret_cast<const uint32_t*>(prm.u)[t * 256 + j * 32 + lane],
                                                  reinterpret_cast<const uint32_t*>(prm.gw)[j * 32 + lane]);
                        s += bf_lo(pr) + bf_hi(pr);
                    }
#pragma unroll
                    for (int o = 16; o > 0; o >>= 1) s += __shfl_xor_sync(0xffffffffu, s, o);
                    if (lane == 0) {
                        const uint32_t wd = gate_word(s);
                        const uint32_t d = sb + OFF_GT + ((t >> 8) * 128 + (t & 127)) * 8 + ((t >> 7) & 1) * 2;
                        asm volatile("st.shared.u16 [%0],%1;\n" :: "r"(d), "h"((uint16_t)(wd & 0xFFFFu)) : "memory");
                        asm volatile("st.shared.u16 [%0],%1;\n" :: "r"(d + 4), "h"((uint16_t)(wd >> 16)) : "memory");
                    }
                }
            }
        }
        asm volatile("bar.sync 1, 128;\n" ::: "memory");
        STAMP(11);
        asm volatile("bar.arrive 10, 256;\n" ::: "memory");
        mbar_wait(sb + OFF_MB_P);
#pragma unroll 1
        for (int b = 0; b < 4; b += (b == 1) ? 2 : 1) {
            final_block(&tm_out, sb, cl, rank, un, b, 1);
            STAMP(5 + b);
        }
        if (un == 0) {
            asm volatile("cp.async.bulk.wait_group.read 0;\n" ::: "memory");
            STAMP(13);
            GSTAMP(1);
        }
        return;
    }

    const int ch = warp & 3, role = warp >> 2;
    const int chg = 8 * cl + 4 * rank + ch;
    const int g = lane >> 2, q = lane & 3;

    uint2 pLA, pAI, pCR, pCI;
    {
        const size_t o = (size_t)chg * 128 + lane * 4;
        pLA = __ldg(reinterpret_cast<const uint2*>(prm.p[role][0] + o));
        pAI = __ldg(reinterpret_cast<const uint2*>(prm.p[role][1] + o));
        pCR = __ldg(reinterpret_cast<const uint2*>(prm.p[role][2] + o));
        pCI = __ldg(reinterpret_cast<const uint2*>(prm.p[role][3] + o));
    }
    const float log_dt = __bfloat162float(prm.p[role][4][chg]);
    const float dskip = __bfloat162float(prm.p[role][5][chg]);

    const uint32_t kt = sb + OFF_KT + warp * KT_W;
    {
        if (lane < 30) sts64(kt + KT_WD1 + (lane < 14 ? lane : 258 + lane) * 8, 0u, 0u);
        const uint32_t z2 = kt + KT_WD4 + (lane < 7 ? lane : 64 + lane) * 4;
        if (lane < 16) { sts32(z2, 0u); sts32(z2 + 320, 0u); }
    }
    float dt = 0.f, fscale = 0.f, cinv = 0.f, f0 = 0.f;
    float dk[5][4];
#pragma unroll
    for (int j = 0; j < 5; ++j) { dk[j][0] = dk[j][1] = dk[j][2] = dk[j][3] = 0.f; }
    {
        const uint32_t tb = sb + OFF_FT + warp * FT_W;
        const int mat = lane >> 3, rr = lane & 7;
        const uint32_t stb = tb + (71 * rr + 8 * (mat & 1)) * 16, stc = tb + (71 * rr + 64 + (mat & 1)) * 16;
        const uint32_t ld0 = tb + ((mat & 1) ? 64 + (mat >> 1) : 8 * (mat >> 1) + rr) * 16;
        const uint32_t ld1 = tb + (16 + 8 * mat + rr) * 16;
        const uint32_t ld2 = tb + ((mat & 2) ? 64 + mat : 48 + 8 * mat + rr) * 16;
        const uint32_t ld3 = tb + (71 * (mat >> 1) + 68 + (mat & 1)) * 16;
#pragma unroll
        for (int r = 0; r < 2; ++r) {
            uint32_t wLA = 0u, wAI = 0u, wCR = 0u, wCI = 0u;
            if (r == 0) {
                dt = bf_round(expf(log_dt));
                uint32_t m = max(max(max(pCR.x & 0x7F80u, (pCR.x >> 16) & 0x7F80u), max(pCR.y & 0x7F80u, (pCR.y >> 16) & 0x7F80u)),
                                 max(max(pCI.x & 0x7F80u, (pCI.x >> 16) & 0x7F80u), max(pCI.y & 0x7F80u, (pCI.y >> 16) & 0x7F80u)));
                m = __reduce_max_sync(0xffffffffu, m) >> 7;
                m = min(max(m, 1u), 253u);
                cinv = __uint_as_float((254u - m) << 23);
                fscale = 2.0f * dt * __uint_as_float(m << 23);
                wLA = pLA.x; wAI = pAI.x; wCR = pCR.x; wCI = pCI.x;
                STAMP(1);
            } else if (r == 1) {
                f0 = (bf_lo(pCR.x) + bf_hi(pCR.x)) + (bf_lo(pCR.y) + bf_hi(pCR.y));
#pragma unroll
                for (int o = 16; o > 0; o >>= 1) f0 += __shfl_xor_sync(0xffffffffu, f0, o);
                f0 = fmaf(2.0f * dt, f0, dskip);
                wLA = pLA.y; wAI = pAI.y; wCR = pCR.y; wCI = pCI.y;
            }
            float ea, eb;
            asm("ex2.approx.ftz.f32 %0,%1;\n" : "=f"(ea) : "f"(bf_lo(wLA) * 1.4426950408889634f));
            asm("ex2.approx.ftz.f32 %0,%1;\n" : "=f"(eb) : "f"(bf_hi(wLA) * 1.4426950408889634f));
            const uint32_t e2 = pack_bf16(ea, eb);
            const float ala = (-bf_lo(e2) * dt) * 1.4426950408889634f, alb = (-bf_hi(e2) * dt) * 1.4426950408889634f;
            const float aia = bf_lo(wAI) * dt, aib = bf_hi(wAI) * dt;
            const pc C = mk64(pack_f16(bf_lo(wCR) * cinv, bf_hi(wCR) * cinv), pack_f16(bf_lo(wCI) * cinv, bf_hi(wCI) * cinv));
            {
                c32 a = cexp_seed(ala, -aia, 16.f), b = cexp_seed(alb, -aib, 16.f);
                const pc f1 = mkp(a, b); a = csq(a); b = csq(b);
                const pc f2 = mkp(a, b); a = csq(a); b = csq(b);
                const pc f4 = mkp(a, b); a = csq(a); b = csq(b);
                stp(stb, 0x3C003C00ull);
                stp(stb + 16, f1); stp(stb + 32, f2); stp(stb + 64, f4); stp(stc, mkp(a, b));
                c32 a256 = csq(a), b256 = csq(b);
                a256.y = -a256.y; b256.y = -b256.y;
                const pc f3 = pmul(f1, f2);
                stp(stb + 48, f3); stp(stb + 80, pmul(f1, f4)); stp(stb + 96, pmul(f2, f4)); stp(stb + 112, pmul(f3, f4));
                a = cexp_seed(ala, aia, 1.f); b = cexp_seed(alb, aib, 1.f);
                const pc w1 = mkp(a, b); a = csq(a); b = csq(b);
                const pc w2 = mkp(a, b); a = csq(a); b = csq(b);
                const pc w4 = mkp(a, b); a = csq(a); b = csq(b);
                const pc w8 = mkp(a, b);
                stp(stc + 32, w1);
                pc D[4];
                D[0] = pmul(C, w1); D[1] = pmul(D[0], w2); D[2] = pmul(D[0], w4); D[3] = pmul(D[1], w4);
#pragma unroll
                for (int j = 0; j < 4; ++j) { stp(stb + 256 + 16 * j, D[j]); stp(stb + 320 + 16 * j, pmul(D[j], w8)); }
                a = a256; b = b256;
                const pc w256 = mkp(a, b); a = csq(a); b = csq(b);
                const pc w512 = mkp(a, b); a = csq(a); b = csq(b);
                const pc w1024 = mkp(a, b);
                stp(stc + 64, w256);
                D[0] = pmul(C, w4); D[1] = pmul(C, w8); D[2] = pmul(D[0], w8); D[3] = pmul(D[1], w8);
#pragma unroll
                for (int j = 0; j < 4; ++j) {
                    const pc t = pmul(D[j], w512);
                    stp(stb + 512 + 16 * j, t); stp(stb + 576 + 16 * j, pmul(t, w256));
                }
#pragma unroll
                for (int j = 0; j < 2; ++j) {
                    const pc t = pmul(D[2 * j + 1], w1024), t2 = pmul(t, w256);
                    stp(stb + 768 + 16 * j, t); stp(stb + 800 + 16 * j, t2);
                    stp(stb + 832 + 16 * j, pmul(t, w512)); stp(stb + 864 + 16 * j, pmul(t2, w512));
                }
            }
            __syncwarp();
#pragma unroll
            for (int s = 0; s < 8; s += 2) {
                uint32_t W[4];
                ldsm4(W, ld3 + s * 1136);
#pragma unroll
                for (int h = 0; h < 2; ++h) {
                    uint32_t L0[4], L1[4], L2[4];
                    ldsm4(L0, ld0 + (s + h) * 1136); ldsm4(L1, ld1 + (s + h) * 1136); ldsm4(L2, ld2 + (s + h) * 1136);
                    uint32_t A[4];
                    A[0] = L0[0]; A[2] = L0[2];
                    asm("{.reg .b32 t0,t1,n; mul.rn.f16x2 t0,%2,%4; mul.rn.f16x2 t1,%3,%4; neg.f16x2 n,%3;\n"
                        "fma.rn.f16x2 %0,n,%5,t0; fma.rn.f16x2 %1,%2,%5,t1;}\n"
                        : "=r"(A[1]), "=r"(A[3]) : "r"(L0[0]), "r"(L0[2]), "r"(L0[1]), "r"(L0[3]));
                    const pc t1 = pmul(mk64(L1[0], L1[1]), mk64(L2[2], L2[3]));
                    const pc t2 = pmul(t1, mk64(W[2 * h], W[2 * h + 1]));
                    mma_f16(dk[0], A, L1[0], L1[1]);
                    mma_f16(dk[3], A, L1[2], L1[3]);
                    mma_f16(dk[4], A, L2[0], L2[1]);
                    mma_f16p(dk[1], A, t1);
                    mma_f16p(dk[2], A, t2);
                }
            }
            __syncwarp();
        }
    }
    STAMP(2);

    {
        const bool last = (lane == 31);
#pragma unroll
        for (int j = 0; j < 5; ++j)
#pragma unroll
            for (int c = 0; c < 4; ++c) dk[j][c] *= fscale;
        const float f256 = dk[1][3], f512 = dk[2][3], f1024 = dk[3][3];
        if (last) { dk[2][2] -= f512; dk[2][3] = 0.f; }
        const float n0 = __shfl_sync(0xffffffffu, dk[0][0], (lane + 1) & 31), n1 = __shfl_sync(0xffffffffu, dk[0][2], (lane + 1) & 31);
        const float p0 = __shfl_sync(0xffffffffu, lane == 31 ? f256 : dk[2][1], (lane + 31) & 31);
        const float p1 = __shfl_sync(0xffffffffu, lane == 31 ? dk[2][1] : dk[2][3], (lane + 31) & 31);
#pragma unroll
        for (int hh = 0; hh < 2; ++hh) {
            const float a = dk[0][2 * hh], b = dk[1][2 * hh], c = dk[0][2 * hh + 1], d = dk[1][2 * hh + 1];
            const float an = hh == 0 ? (last ? n1 : n0) : (last ? d : n1);
            const uint32_t wa = kt + KT_WD1 + (16 + 4 * lane + 128 * hh) * 8;
            const float be = dk[2][2 * hh], al = dk[2][2 * hh + 1];
            const uint32_t aa = pack_bf16(al, al);
            const uint32_t w0 = pack_bf16(b, a), w1 = pack_bf16(c, b), w2 = pack_bf16(d, c), w3 = pack_bf16(an, d);
            sts128(wa, w0, pack_bf16(be, hh == 0 ? p0 : p1), w1, pack_bf16(al, be));
            sts128(wa + 16, w2, aa, w3, aa);
            if (hh == 1 && lane >= 28) {
                sts32(wa - 2048 + 4, w0); sts32(wa - 2048 + 12, w1); sts32(wa - 2048 + 20, w2); sts32(wa - 2048 + 28, w3);
            }
        }
        if (lane == 0) { sts32(kt + KT_WD1 + 14 * 8, pack_bf16(f0, 0.f)); sts32(kt + KT_WD1 + 15 * 8, pack_bf16(dk[0][0], f0)); }
        if (warp == 4) asm volatile("bar.arrive 2, 288;\n" ::: "memory");
#pragma unroll
        for (int hh = 0; hh < 2; ++hh) {
            const int i = g + 8 * hh;
            sts32(kt + KT_WD4 + (2 * i + (q & 1) + 32 * (q >> 1) + 8) * 4, pack_bf16(dk[3][2 * hh + 1], dk[3][2 * hh]));
            sts32(kt + KT_WD4 + 320 + (i + 16 * q + 7) * 4, pack_bf16(dk[4][2 * hh + 1], dk[4][2 * hh]));
        }
        if (last) {
            const uint32_t w512 = pack_bf16(f512, 0.f);
            sts32(kt + KT_WD4 + 7 * 4, w512);
            sts128(kt + KT_WD1 + 274 * 8, w512, 0u, w512, 0u);
            sts32(kt + KT_FIX, pack_bf16(f1024, f1024));
        }
    }
    STAMP(3);
    if (role) {
        asm volatile("bar.arrive 13, 256;\n" ::: "memory");
    } else {
        asm volatile("bar.sync 2, 288;\n" ::: "memory");
    }
    STAMP(6);

    const uint32_t ktA = sb + OFF_KT + ch * KT_W, ktB = ktA + 4 * KT_W;
    const int mat = lane >> 3, rr = lane & 7;
    const int np = 4 * (g & 1) + (g >> 1);
    uint32_t k4[9][2][2], k8[8][2][2], kf[2];
    const uint32_t o4 = KT_WD4 + (g - q + 7) * 4;
    const uint32_t o8 = KT_WD4 + 320 + (np + 7 - q) * 4;
#define K_LOAD(DST, OFF, KS)                                                                                 \
        { DST[KS][0][0] = lds32(ktA + OFF + (8 * (KS)) * 4); DST[KS][0][1] = lds32(ktA + OFF + (8 * (KS) - 4) * 4); \
          DST[KS][1][0] = lds32(ktB + OFF + (8 * (KS)) * 4); DST[KS][1][1] = lds32(ktB + OFF + (8 * (KS) - 4) * 4); }
    {
        const int rb = ch >> 1, br = ch & 1;
        const int urole = __shfl_sync(0xffffffffu, role, 0);
        uint32_t wa = sb + OFF_KT + (br * 4 + role) * KT_W + KT_WD1 + (14 + 8 * rb + g - 2 * q) * 8;
        uint2 af[17][2];
#define A_LOAD(S)                                                                                            \
        if ((S) < 16) { af[S][0] = lds64(wa + 128 * (S)); af[S][1] = lds64(wa + 128 * (S) - 64); }           \
        else { af[S][0] = make_uint2(0u, lds32(wa + 128 * (S) + 4)); af[S][1] = make_uint2(0u, lds32(wa + 128 * (S) - 60)); }
        if (urole) asm volatile("bar.sync 9, 384;\n" ::: "memory");
#pragma unroll
        for (int s = 0; s < 9; ++s) { A_LOAD(s) }
#pragma unroll 1
        for (int cc = 0; cc < 2; ++cc) {
#pragma unroll
            for (int s = 9; s < 17; ++s) { A_LOAD(s) }
            const int c = urole + 2 * cc;
            const uint32_t desc = (((sb + OFF_V + c * V_CH + 256) & 0x3FFFFu) >> 4) | ((V_H >> 4) << 16);
            float d[64];
            if (urole | cc) asm volatile("bar.sync %0, 256;\n" :: "r"(5 + urole) : "memory");
            else asm volatile("bar.arrive 9, 384;\n" ::: "memory");
            asm volatile("wgmma.fence.sync.aligned;\n" ::: "memory");
#pragma unroll
            for (int s = 0; s < 9; ++s) wgmma_n128(d, af[s][0].x, af[s][0].y, af[s][1].x, af[s][1].y, desc - s, s);
            asm volatile("wgmma.commit_group.sync.aligned;\n" ::: "memory");
#pragma unroll
            for (int s = 9; s < 17; ++s)
                wgmma_n128(d, af[s][0].x, af[s][0].y, af[s][1].x, af[s][1].y, desc - s, 1);
            asm volatile("wgmma.commit_group.sync.aligned;\n" ::: "memory");
            if (!(urole & cc)) asm volatile("bar.arrive %0, 256;\n" :: "r"(6 - urole) : "memory");
            if (!(urole | cc)) asm volatile("bar.sync 13, 256;\n" ::: "memory");
            asm volatile("wgmma.wait_group.sync.aligned 1;\n" ::: "memory");
            wa += 2 * KT_W;
            if (cc == 0) {
#pragma unroll
                for (int s = 0; s < 9; ++s) { A_LOAD(s) }
            }
            asm volatile("wgmma.wait_group.sync.aligned 0;\n" ::: "memory");
#pragma unroll
            for (int i = 0; i < 64; ++i) asm volatile("" : "+f"(d[i]) :: "memory");
            if (urole & cc) asm volatile("bar.arrive 7, 256;\n" ::: "memory");
            if (cc == 0) STAMP(4); else STAMP(5);
            if (rb == 1 && (lane | 4) == 31) {
                const uint32_t u01 = lds32(sb + OFF_V + c * V_CH + 256);
                const float f512 = bf_lo(lds32(wa - 2 * KT_W + 252 * 8));
                d[13] = fmaf(f512, lane == 27 ? bf_lo(u01) : bf_lo(u01) + bf_hi(u01), d[13]);
            }
            const uint32_t dst = sb + OFF_S1P + c * 8192 + br * 4096 + (32 * q + g) * 4;
#pragma unroll
            for (int j = 0; j < 16; j += 2)
#pragma unroll
                for (int e = 0; e < 2; ++e) {
                    const float y0 = j >= 2 ? d[4 * j + e] + d[4 * j - 6 + e] : d[4 * j + e];
                    const float y1 = j >= 2 ? d[4 * j + 4 + e] + d[4 * j - 2 + e] : d[4 * j + 4 + e];
                    sts32(dst + j * 256 + ((16 * e + 8 * rb) ^ (8 * q)) * 4, pack_bf16(y0, y1));
                }
            __syncwarp();
            if (lane == 0) mbar_arrive(sb + OFF_MB_P);
        }
#undef A_LOAD
    }
    STAMP(7);

    {
        const uint32_t s2 = sb + OFF_SG2 + ch * SG2_CH;
        const uint32_t b4 = s2 + ((rr & 1) ? G2_W3 : G2_W5) + (18 + 9 * (mat & 1) + 4 * (mat >> 1) + (rr >> 1)) * 16;
        const int d8 = 6 + 8 * (mat >> 1) + rr + (mat & 1);
        const uint32_t b8 = s2 + ((rr & 1) ? ((d8 & 1) ? G2_W7O : G2_W7E) : ((d8 & 1) ? G2_W9O : G2_W9E)) + (d8 >> 1) * 16;
        const uint32_t bf = s2 + ((mat & 1) ? G2_P2O : G2_P2E) + rr * 16;
        const uint32_t pg = sb + OFF_PG2 + ch * 6144 + (32 * (q >> 1) + g) * 4;
        const int blk = 2 + role;
        const uint32_t c8 = b8 + (4 * blk - 8) * 128, c4 = b4 + (8 * blk - 8) * 144;
#define G2_STORE(ACC, BLK)                                                                                   \
        _Pragma("unroll") for (int tj = 0; tj < 4; tj += 2)                                                  \
            _Pragma("unroll") for (int br = 0; br < 2; ++br)                                                 \
                _Pragma("unroll") for (int c = 0; c < 4; ++c)                                                \
                    sts32(pg + br * 3072 + ((BLK) - 1) * 1024 + tj * 256 + (c >> 1) * 256 +                  \
                          (16 * ((q & 1) ^ (c >> 1)) + 8 * ((c & 1) ^ (q >> 1))) * 4,                        \
                          pack_bf16(ACC[tj][br][c], ACC[tj + 1][br][c]));                                    \
        __syncwarp();                                                                                         \
        if (lane == 0) mbar_arrive(sb + OFF_MB_P + 8 * (BLK));
        uint32_t fa[4], fb[4], fc[4], fd[4], fx[4][2];
#pragma unroll
        for (int ks = 0; ks < 9; ++ks) K_LOAD(k4, o4, ks);
        {
            const uint32_t msk = ((np >> 1) == q) ? ((np & 1) ? 0xFFFF0000u : 0x0000FFFFu) : 0u;
            kf[0] = lds32(ktA + KT_FIX) & msk; kf[1] = lds32(ktB + KT_FIX) & msk;
        }
#pragma unroll
        for (int ks = 0; ks < 4; ++ks) K_LOAD(k8, o8, ks);
        if (role) {
#pragma unroll
            for (int ks = 4; ks < 8; ++ks) K_LOAD(k8, o8, ks);
        }
        asm volatile("bar.sync %0, 256;\n" :: "r"(3 + role) : "memory");
        STAMP(8);
        float a8[4][2][4];
#pragma unroll
        for (int tj = 0; tj < 4; ++tj)
#pragma unroll
            for (int br = 0; br < 2; ++br) { a8[tj][br][0] = a8[tj][br][1] = a8[tj][br][2] = a8[tj][br][3] = 0.f; }
        if (role == 0) {
            ldsm4t(fa, b4 - 2 * 144); ldsm4t(fb, b4 - 144);
            asm volatile("bar.sync 7, 256;\n" ::: "memory");
            float a1[4][2][4];
#pragma unroll
            for (int tj = 0; tj < 4; ++tj)
#pragma unroll
                for (int br = 0; br < 2; ++br) { a1[tj][br][0] = a1[tj][br][1] = a1[tj][br][2] = a1[tj][br][3] = 0.f; }
            toep_block<2, 8, -2, 6, 144>(a1, k4, b4, fa, fb);
            G2_STORE(a1, 1);
            STAMP(9);
        } else {
            ldsm4t(fc, b8); ldsm4t(fd, b8 + 128);
            toep_block<1, 7, -4, -1, 128>(a8, k8, b8 + 4 * 128, fc, fd);
        }
#pragma unroll
        for (int tj = 0; tj < 4; ++tj) ldsm2t(fx[tj][0], fx[tj][1], bf + (4 * blk - 8 + tj) * 128);
        ldsm4t(fc, c8); ldsm4t(fd, c8 + 128);
        ldsm4t(fa, c4 - 8 * 144); ldsm4t(fb, c4 - 7 * 144);
#pragma unroll
        for (int tj = 0; tj < 4; ++tj) { mma_bf16_k8(a8[tj][0], fx[tj][0], fx[tj][1], kf[0]); mma_bf16_k8(a8[tj][1], fx[tj][0], fx[tj][1], kf[1]); }
        toep_block<1, 7, 0, 3, 128>(a8, k8, c8, fc, fd);
        float a4[4][2][4];
#pragma unroll
        for (int tj = 0; tj < 4; ++tj)
#pragma unroll
            for (int br = 0; br < 2; ++br) {
                a4[tj][br][0] = a8[tj][br][0]; a4[tj][br][1] = a8[tj][br][2];
                a4[tj][br][2] = a8[tj][br][1]; a4[tj][br][3] = a8[tj][br][3];
            }
        toep_block<2, 8, -8, 6, 144>(a4, k4, c4, fa, fb);
        G2_STORE(a4, blk);
        STAMP(10);
#undef G2_STORE
#undef K_LOAD
    }
    asm volatile("barrier.cluster.wait.acquire.aligned;\n" ::: "memory");
    if (role == 0) {
        asm volatile("bar.sync 10, 256;\n" ::: "memory");
        mbar_wait(sb + OFF_MB_P);
        final_block(&tm_out, sb, cl, rank, tid, 2, 11);
        STAMP(11);
        if (tid == 0) asm volatile("cp.async.bulk.wait_group.read 0;\n" ::: "memory");
    }
}

typedef CUresult (*EncodeFn)(CUtensorMap*, CUtensorMapDataType, cuuint32_t, void*, const cuuint64_t*, const cuuint64_t*,
                             const cuuint32_t*, const cuuint32_t*, CUtensorMapInterleave, CUtensorMapSwizzle,
                             CUtensorMapL2promotion, CUtensorMapFloatOOBfill);

}

extern "C" void kernel_launch(void* const* d_in, const int* in_sizes, int n_in, void* d_out, int out_size) {
    (void)in_sizes; (void)n_in; (void)out_size;
    static EncodeFn encode = nullptr;
    if (!encode) {
        void* fn = nullptr;
        cudaDriverEntryPointQueryResult qr;
        cudaGetDriverEntryPoint("cuTensorMapEncodeTiled", &fn, cudaEnableDefault, &qr);
        encode = (EncodeFn)fn;
        cudaFuncSetAttribute(fused_s4d_kernel, cudaFuncAttributeMaxDynamicSharedMemorySize, SMEM_BYTES);
    }
    CUtensorMap tin, tout;
    {
        cuuint64_t gd[3] = {DCH, 128, 16};
        cuuint64_t gs[2] = {16 * 1024, 1024};
        cuuint32_t bx[3] = {8, 128, 8};
        cuuint32_t es[3] = {1, 1, 1};
        encode(&tin, CU_TENSOR_MAP_DATA_TYPE_BFLOAT16, 3, d_in[0], gd, gs, bx, es, CU_TENSOR_MAP_INTERLEAVE_NONE,
               CU_TENSOR_MAP_SWIZZLE_NONE, CU_TENSOR_MAP_L2_PROMOTION_NONE, CU_TENSOR_MAP_FLOAT_OOB_FILL_NONE);
    }
    {
        cuuint64_t gd[4] = {DCH, 128, 2, 8};
        cuuint64_t gs[3] = {2048, 1024, 256 * 1024};
        cuuint32_t bx[4] = {8, 64, 2, 2};
        cuuint32_t es[4] = {1, 1, 1, 1};
        encode(&tout, CU_TENSOR_MAP_DATA_TYPE_BFLOAT16, 4, d_out, gd, gs, bx, es, CU_TENSOR_MAP_INTERLEAVE_NONE,
               CU_TENSOR_MAP_SWIZZLE_NONE, CU_TENSOR_MAP_L2_PROMOTION_NONE, CU_TENSOR_MAP_FLOAT_OOB_FILL_NONE);
    }
    Params prm;
    prm.u = (const __nv_bfloat16*)d_in[0];
    for (int j = 0; j < 6; ++j) {
        prm.p[0][j] = (const __nv_bfloat16*)d_in[1 + j];
        prm.p[1][j] = (const __nv_bfloat16*)d_in[8 + j];
    }
    prm.gw = (const __nv_bfloat16*)d_in[14];
    fused_s4d_kernel<<<128, NTHREADS, SMEM_BYTES, cudaStreamPerThread>>>(prm, tin, tout);
}
```
